```python
import torch

def _softmax(x, axis=-1):
    return torch.softmax(x, dim=axis)

def _gelu(x):
    return torch.nn.functional.gelu(x, approximate='tanh')

def _silu(x):
    return torch.nn.functional.silu(x)

def _sigmoid(x):
    return torch.sigmoid(x)

def _layernorm(x, axis=-1, eps=1e-05):
    m = x.mean(dim=axis, keepdim=True)
    v = x.var(dim=axis, keepdim=True, unbiased=False)
    return (x - m) / torch.sqrt(v + eps)

def _scatter_add(tgt, idx, src, axis=0):
    return tgt.clone().index_add_(axis, idx, src)

def _segment_sum(src, seg, n):
    out = torch.zeros((n,) + src.shape[1:], dtype=src.dtype)
    return out.index_add_(0, seg, src)

def _pad(x, pw):
    flat = tuple((v for pair in reversed(pw) for v in pair))
    return torch.nn.functional.pad(x, flat)
kernel_name = 'recurrent_scan__sliding_block_cached__mixer_gmlp__prompt'

def setup_inputs():

    _w = lambda a: (lambda t: t.to(torch.bfloat16) if t.is_floating_point() else t)(torch.as_tensor(a))

    def _A_setup():
        B, Sq, D = (1, 2048, 1024)
        Hq, Hkv, Sk, Dh = (32, 4, 2048, 128)
        assert Hq % Hkv == 0, (Hq, Hkv)
        return {'x': _w((lambda *s: torch.randn(*s, dtype=torch.bfloat16) * 0.05)(B, Sq, D)), 'k_cache': _w((lambda *s: torch.randn(*s, dtype=torch.bfloat16) * 0.8)(B, Hkv, Sk, Dh)), 'v_cache': _w((lambda *s: torch.randn(*s, dtype=torch.bfloat16) * 0.2)(B, Hkv, Sk, Dh)), 'wq': _w((lambda *s: torch.randn(*s, dtype=torch.bfloat16) * 0.8)(D, Hq * Dh) * D ** (-0.5)), 'wo': _w((lambda *s: torch.randn(*s, dtype=torch.bfloat16) * 0.2)(Hq * Dh, D) * (Hq * Dh) ** (-0.5))}
    _A_in = _A_setup()

    def _B_setup():
        B, S, D, F = (1, 2048, 1024, 3584)
        Fh = F // 2
        return {'x': _w((lambda *s: torch.randn(*s, dtype=torch.bfloat16) * 0.05)(B, S, D)), 'w_in': _w((lambda *s: torch.randn(*s, dtype=torch.bfloat16) * 0.4)(D, 2 * Fh)), 'w_sp': _w(0.01 * (lambda *s: torch.randn(*s, dtype=torch.bfloat16) * 0.4)(S, S)), 'b_sp': _w(1.0 + 0.01 * (lambda *s: torch.randn(*s, dtype=torch.bfloat16) * 0.1)(S)), 'w_out': _w((lambda *s: torch.randn(*s, dtype=torch.bfloat16) * 0.1)(Fh, D))}
    _B_in = _B_setup()
    return {'A_x': _A_in['x'], 'A_k_cache': _A_in['k_cache'], 'A_v_cache': _A_in['v_cache'], 'A_wq': _A_in['wq'], 'A_wo': _A_in['wo'], 'B_x': _B_in['x'], 'B_w_in': _B_in['w_in'], 'B_w_sp': _B_in['w_sp'], 'B_b_sp': _B_in['b_sp'], 'B_w_out': _B_in['w_out']}

def reference(A_x, A_k_cache, A_v_cache, A_wq, A_wo, B_x, B_w_in, B_w_sp, B_b_sp, B_w_out):

    def _A_ref(x, k_cache, v_cache, wq, wo):
        B, Sq, D = x.shape
        Hq, Dh = (32, 128)
        Hkv, Sk = (k_cache.shape[1], k_cache.shape[2])
        W = min(4096, max(256, Sk // 4))
        rep = Hq // Hkv
        q = (lambda x, *d: x.permute(*d))((x @ wq).reshape(B, Sq, Hq, Dh), 0, 2, 1, 3)
        k = (lambda x, n, axis: torch.repeat_interleave(x, n, dim=axis))(k_cache[:, :, Sk - W:, :], rep, axis=1)
        v = (lambda x, n, axis: torch.repeat_interleave(x, n, dim=axis))(v_cache[:, :, Sk - W:, :], rep, axis=1)
        scores = torch.einsum('bhqd,bhkd->bhqk', q, k) * Dh ** (-0.5)
        p = _softmax(scores, axis=-1)
        o = torch.einsum('bhqk,bhkd->bhqd', p, v)
        return (lambda x, *d: x.permute(*d))(o, 0, 2, 1, 3).reshape(B, Sq, Hq * Dh) @ wo

    def _B_ref(x, w_in, w_sp, b_sp, w_out):
        B, S, D = x.shape
        F = w_in.shape[-1]
        Fh = F // 2
        z = _gelu(torch.einsum('bsd,df->bsf', x, w_in))
        z1 = z[..., :Fh].clone()
        z2 = _layernorm(z[..., Fh:], axis=-1)
        g = torch.einsum('ts,bsf->btf', w_sp, z2) + b_sp[None, :, None]
        return torch.einsum('bsf,fd->bsd', z1 * g, w_out)
    x = A_x
    xn = _layernorm(x, axis=-1)
    s = _A_ref(xn, A_k_cache, A_v_cache, A_wq, A_wo)
    g = _silu(_B_ref(xn, B_w_in, B_w_sp, B_b_sp, B_w_out))
    return x + s * g
```

```cpp
#include <cuda_runtime.h>
#include <cuda_bf16.h>
#include <cuda.h>
#include <stdint.h>

typedef __nv_bfloat16 bf16;

constexpr int SEQ = 2048, DM = 1024, HD = 4096, FF = 3584, FH = 1792, SK = 2048, WIN = 512;
constexpr int NCLUSTERS = 64;
constexpr int MAXT = 10;

__device__ bf16 g_xn[SEQ * DM];
__device__ bf16 g_z2[SEQ * FH];
__device__ bf16 g_o[SEQ * HD];
__device__ bf16 g_h[SEQ * FH];
__device__ bf16 g_sy[SEQ * DM];
constexpr int F_XN = 0;
constexpr int F_Z2N = 16;
constexpr int F_ST = 32;
constexpr int F_O = 64;
constexpr int F_H = 576;
constexpr int F_SY = 704;
constexpr int F_TICKET = 768;
constexpr int F_COUNT = 800;
__device__ __align__(16) unsigned int g_flags[F_COUNT];
__device__ float2 g_stats[7 * SEQ];

enum { M_XN = 0, M_WSP, M_O_LD, M_H_LD, M_X, M_SY_LD, M_K, M_V,
       M_WIN, M_WQ, M_Z2, M_WO, M_WOUT,
       M_Z2_ST, M_O_ST, M_H_ST, M_SY_ST, M_OUT,
       M_COUNT };
enum { T_NONE = 0, T_Z2, T_QA, T_Z1, T_G, T_SP, T_Y, T_SF };

struct Params {
  CUtensorMap maps[M_COUNT];
  const bf16* x;
  const bf16* b_sp;
  unsigned short tasks[NCLUSTERS][MAXT + 1];
  unsigned char krange[NCLUSTERS][2];
};

constexpr int STAGES = 4;
constexpr int STAGE_BYTES = 49152;
constexpr int SM_STG = STAGES * STAGE_BYTES;
constexpr int SM_BAR = SM_STG + 32768;
constexpr int SM_STAT = SM_BAR + 256;
constexpr int SMEM_BYTES = SM_STAT + 1024 + 1024;

template <int TB>
__device__ __forceinline__ void wgmma_ss_n128(float (&d)[64], uint64_t da, uint64_t db, int scale_d) {
  asm volatile("{\n.reg .pred p;\nsetp.ne.b32 p, %66, 0;\n"
    "wgmma.mma_async.sync.aligned.m64n128k16.f32.bf16.bf16 {%0, %1, %2, %3, %4, %5, %6, %7, %8, %9, %10, %11, %12, %13, %14, %15, %16, %17, %18, %19, %20, %21, %22, %23, %24, %25, %26, %27, %28, %29, %30, %31, %32, %33, %34, %35, %36, %37, %38, %39, %40, %41, %42, %43, %44, %45, %46, %47, %48, %49, %50, %51, %52, %53, %54, %55, %56, %57, %58, %59, %60, %61, %62, %63}, %64, %65, p, 1, 1, 0, %67;\n}\n"
    : "+f"(d[0]), "+f"(d[1]), "+f"(d[2]), "+f"(d[3]), "+f"(d[4]), "+f"(d[5]), "+f"(d[6]), "+f"(d[7]), "+f"(d[8]), "+f"(d[9]), "+f"(d[10]), "+f"(d[11]), "+f"(d[12]), "+f"(d[13]), "+f"(d[14]), "+f"(d[15]), "+f"(d[16]), "+f"(d[17]), "+f"(d[18]), "+f"(d[19]), "+f"(d[20]), "+f"(d[21]), "+f"(d[22]), "+f"(d[23]), "+f"(d[24]), "+f"(d[25]), "+f"(d[26]), "+f"(d[27]), "+f"(d[28]), "+f"(d[29]), "+f"(d[30]), "+f"(d[31]), "+f"(d[32]), "+f"(d[33]), "+f"(d[34]), "+f"(d[35]), "+f"(d[36]), "+f"(d[37]), "+f"(d[38]), "+f"(d[39]), "+f"(d[40]), "+f"(d[41]), "+f"(d[42]), "+f"(d[43]), "+f"(d[44]), "+f"(d[45]), "+f"(d[46]), "+f"(d[47]), "+f"(d[48]), "+f"(d[49]), "+f"(d[50]), "+f"(d[51]), "+f"(d[52]), "+f"(d[53]), "+f"(d[54]), "+f"(d[55]), "+f"(d[56]), "+f"(d[57]), "+f"(d[58]), "+f"(d[59]), "+f"(d[60]), "+f"(d[61]), "+f"(d[62]), "+f"(d[63])
    : "l"(da), "l"(db), "r"(scale_d), "n"(TB));
}
template <int TB>
__device__ __forceinline__ void wgmma_rs_n128(float (&d)[64], uint32_t a0, uint32_t a1, uint32_t a2, uint32_t a3, uint64_t db, int scale_d) {
  asm volatile("{\n.reg .pred p;\nsetp.ne.b32 p, %69, 0;\n"
    "wgmma.mma_async.sync.aligned.m64n128k16.f32.bf16.bf16 {%0, %1, %2, %3, %4, %5, %6, %7, %8, %9, %10, %11, %12, %13, %14, %15, %16, %17, %18, %19, %20, %21, %22, %23, %24, %25, %26, %27, %28, %29, %30, %31, %32, %33, %34, %35, %36, %37, %38, %39, %40, %41, %42, %43, %44, %45, %46, %47, %48, %49, %50, %51, %52, %53, %54, %55, %56, %57, %58, %59, %60, %61, %62, %63}, {%64, %65, %66, %67}, %68, p, 1, 1, %70;\n}\n"
    : "+f"(d[0]), "+f"(d[1]), "+f"(d[2]), "+f"(d[3]), "+f"(d[4]), "+f"(d[5]), "+f"(d[6]), "+f"(d[7]), "+f"(d[8]), "+f"(d[9]), "+f"(d[10]), "+f"(d[11]), "+f"(d[12]), "+f"(d[13]), "+f"(d[14]), "+f"(d[15]), "+f"(d[16]), "+f"(d[17]), "+f"(d[18]), "+f"(d[19]), "+f"(d[20]), "+f"(d[21]), "+f"(d[22]), "+f"(d[23]), "+f"(d[24]), "+f"(d[25]), "+f"(d[26]), "+f"(d[27]), "+f"(d[28]), "+f"(d[29]), "+f"(d[30]), "+f"(d[31]), "+f"(d[32]), "+f"(d[33]), "+f"(d[34]), "+f"(d[35]), "+f"(d[36]), "+f"(d[37]), "+f"(d[38]), "+f"(d[39]), "+f"(d[40]), "+f"(d[41]), "+f"(d[42]), "+f"(d[43]), "+f"(d[44]), "+f"(d[45]), "+f"(d[46]), "+f"(d[47]), "+f"(d[48]), "+f"(d[49]), "+f"(d[50]), "+f"(d[51]), "+f"(d[52]), "+f"(d[53]), "+f"(d[54]), "+f"(d[55]), "+f"(d[56]), "+f"(d[57]), "+f"(d[58]), "+f"(d[59]), "+f"(d[60]), "+f"(d[61]), "+f"(d[62]), "+f"(d[63])
    : "r"(a0), "r"(a1), "r"(a2), "r"(a3), "l"(db), "r"(scale_d), "n"(TB));
}

__device__ __forceinline__ uint32_t smem_u32(const void* p) { return (uint32_t)__cvta_generic_to_shared(p); }
__device__ __forceinline__ void mbar_init(uint32_t bar, uint32_t cnt) { asm volatile("mbarrier.init.shared::cta.b64 [%0], %1;" ::"r"(bar), "r"(cnt) : "memory"); }
__device__ __forceinline__ void mbar_expect_tx(uint32_t bar, uint32_t bytes) { asm volatile("mbarrier.arrive.expect_tx.shared::cta.b64 _, [%0], %1;" ::"r"(bar), "r"(bytes) : "memory"); }
__device__ __forceinline__ void mbar_arrive(uint32_t bar) { asm volatile("mbarrier.arrive.shared::cta.b64 _, [%0];" ::"r"(bar) : "memory"); }
__device__ __forceinline__ void mbar_arrive_cluster(uint32_t bar, uint32_t cta) {
  asm volatile("{\n.reg .b32 ra;\nmapa.shared::cluster.u32 ra, %0, %1;\nmbarrier.arrive.shared::cluster.b64 _, [ra];\n}\n" ::"r"(bar), "r"(cta) : "memory");
}
__device__ __forceinline__ void mbar_wait(uint32_t bar, uint32_t parity) {
  asm volatile(
      "{\n.reg .pred p;\n.reg .u32 n;\nmov.u32 n, 0;\n"
      "LAB_WAIT:\nmbarrier.try_wait.parity.shared::cta.b64 p, [%0], %1;\n@p bra LAB_DONE;\n"
      "add.u32 n, n, 1;\nsetp.lt.u32 p, n, 4194304;\n@p bra LAB_WAIT;\ntrap;\nLAB_DONE:\n}\n" ::"r"(bar), "r"(parity) : "memory");
}
__device__ __forceinline__ void tma_load_2d(uint32_t dst, const CUtensorMap* tm, uint32_t bar, int c0, int c1) {
  asm volatile("cp.async.bulk.tensor.2d.shared::cluster.global.mbarrier::complete_tx::bytes [%0], [%1, {%3, %4}], [%2];" ::"r"(dst), "l"(tm), "r"(bar), "r"(c0), "r"(c1) : "memory");
}
__device__ __forceinline__ void tma_load_2d_mc(uint32_t dst, const CUtensorMap* tm, uint32_t bar, int c0, int c1) {
  asm volatile("cp.async.bulk.tensor.2d.shared::cluster.global.mbarrier::complete_tx::bytes.multicast::cluster [%0], [%1, {%3, %4}], [%2], %5;" ::"r"(dst), "l"(tm), "r"(bar), "r"(c0), "r"(c1), "h"((uint16_t)3) : "memory");
}
__device__ __forceinline__ void tma_load_3d_mc(uint32_t dst, const CUtensorMap* tm, uint32_t bar, int row, int chunk) {
  asm volatile("cp.async.bulk.tensor.3d.shared::cluster.global.mbarrier::complete_tx::bytes.multicast::cluster [%0], [%1, {%3, %4, %5}], [%2], %6;" ::"r"(dst), "l"(tm), "r"(bar), "r"(0), "r"(row), "r"(chunk), "h"((uint16_t)3) : "memory");
}
__device__ __forceinline__ void tma_store_2d(const CUtensorMap* tm, uint32_t src, int col, int row) {
  asm volatile("cp.async.bulk.tensor.2d.global.shared::cta.bulk_group [%0, {%2, %3}], [%1];" ::"l"(tm), "r"(src), "r"(col), "r"(row) : "memory");
}
__device__ __forceinline__ void wgmma_fence() { asm volatile("wgmma.fence.sync.aligned;" ::: "memory"); }
__device__ __forceinline__ void wgmma_commit() { asm volatile("wgmma.commit_group.sync.aligned;" ::: "memory"); }
template <int N> __device__ __forceinline__ void wgmma_wait() { asm volatile("wgmma.wait_group.sync.aligned %0;" ::"n"(N) : "memory"); }
__device__ __forceinline__ void fence_async() { asm volatile("fence.proxy.async.global;" ::: "memory"); }
__device__ __forceinline__ void fence_async_smem() { asm volatile("fence.proxy.async.shared::cta;" ::: "memory"); }
__device__ __forceinline__ void cluster_arrive() { asm volatile("barrier.cluster.arrive.release;" ::: "memory"); }
__device__ __forceinline__ void cluster_arrive_relaxed() { asm volatile("barrier.cluster.arrive.relaxed;" ::: "memory"); }
__device__ __forceinline__ void cluster_wait() { asm volatile("barrier.cluster.wait.acquire;" ::: "memory"); }
__device__ __forceinline__ void bar_sync(int id, int n) { asm volatile("bar.sync %0, %1;" ::"r"(id), "r"(n) : "memory"); }
__device__ __forceinline__ void bar_arrive(int id, int n) { asm volatile("bar.arrive %0, %1;" ::"r"(id), "r"(n) : "memory"); }
__device__ __forceinline__ uint32_t ld_relaxed(const unsigned int* p) {
  uint32_t v; asm volatile("ld.relaxed.gpu.global.u32 %0, [%1];" : "=r"(v) : "l"(p) : "memory"); return v;
}
__device__ __forceinline__ void fence_acquire() { asm volatile("fence.acquire.gpu;" ::: "memory"); }
__device__ __forceinline__ void red_release(unsigned int* p) { asm volatile("red.release.gpu.global.add.u32 [%0], 1;" ::"l"(p) : "memory"); }
__device__ __forceinline__ void flag_wait(int idx, uint32_t target) {
  uint32_t n = 0;
  while ((int)(ld_relaxed(&g_flags[idx]) - target) < 0) {
    __nanosleep(20);
    if (++n > (1u << 22)) __trap();
  }
  fence_acquire();
}
__device__ __forceinline__ uint64_t make_desc(uint32_t addr, uint32_t lbo, uint32_t sbo) {
  return (uint64_t)((addr & 0x3FFFF) >> 4) | ((uint64_t)(lbo >> 4) << 16) | ((uint64_t)(sbo >> 4) << 32) | (1ull << 62);
}
__device__ __forceinline__ uint32_t pack_bf16(float lo, float hi) {
  uint32_t r; asm("cvt.rn.bf16x2.f32 %0, %1, %2;" : "=r"(r) : "f"(hi), "f"(lo)); return r;
}
__device__ __forceinline__ float bf_lo(uint32_t v) { return __uint_as_float(v << 16); }
__device__ __forceinline__ float bf_hi(uint32_t v) { return __uint_as_float(v & 0xffff0000u); }
__device__ __forceinline__ float ex2(float x) { float r; asm("ex2.approx.ftz.f32 %0, %1;" : "=f"(r) : "f"(x)); return r; }
__device__ __forceinline__ float tanh_fast(float x) { float r; asm("tanh.approx.f32 %0, %1;" : "=f"(r) : "f"(x)); return r; }
__device__ __forceinline__ float gelu2_tanh(float x) {
  float u = x * fmaf(x * x, 0.0356774081f, 0.7978845608f);
  return fmaf(x, tanh_fast(u), x);
}
__device__ __forceinline__ uint32_t mul_bf2(uint32_t a, uint32_t b) { uint32_t r; asm("mul.rn.bf16x2 %0, %1, %2;" : "=r"(r) : "r"(a), "r"(b)); return r; }
__device__ __forceinline__ uint32_t fma_bf2(uint32_t a, uint32_t b, uint32_t c) { uint32_t r; asm("fma.rn.bf16x2 %0, %1, %2, %3;" : "=r"(r) : "r"(a), "r"(b), "r"(c)); return r; }
__device__ __forceinline__ float silu(float y) {
  float r; asm("rcp.approx.ftz.f32 %0, %1;" : "=f"(r) : "f"(1.0f + ex2(-1.4426950409f * y)));
  return y * r;
}
__device__ __forceinline__ void stmatrix_x4(uint32_t addr, uint32_t r0, uint32_t r1, uint32_t r2, uint32_t r3) {
  asm volatile("stmatrix.sync.aligned.m8n8.x4.shared.b16 [%0], {%1, %2, %3, %4};" ::"r"(addr), "r"(r0), "r"(r1), "r"(r2), "r"(r3) : "memory");
}
__device__ __forceinline__ void ldmatrix_x4(uint32_t addr, uint32_t& r0, uint32_t& r1, uint32_t& r2, uint32_t& r3) {
  asm volatile("ldmatrix.sync.aligned.m8n8.x4.shared.b16 {%0, %1, %2, %3}, [%4];" : "=r"(r0), "=r"(r1), "=r"(r2), "=r"(r3) : "r"(addr) : "memory");
}

struct Ctx {
  uint32_t sbase;
  uint32_t bars;
  uint32_t it;
  uint32_t sc;
  uint32_t stg;
  uint32_t st_off;
  uint32_t st_sw;
  int wg, t;
};
__device__ __forceinline__ uint32_t stage_addr(const Ctx& c, uint32_t it) { return c.sbase + (it & 3) * STAGE_BYTES; }
__device__ __forceinline__ void wait_full(const Ctx& c, uint32_t it) { mbar_wait(c.bars + 8 * (it & 3), (it >> 2) & 1); }
__device__ __forceinline__ void release(const Ctx& c, uint32_t it) {
  if (c.t < 2) mbar_arrive_cluster(c.bars + 32 + 8 * (it & 3), c.t);
}
template <int HALF>
__device__ __forceinline__ void mma_half(const Ctx& c, float (&acc)[64], uint32_t it, int first_scale) {
  uint32_t a = stage_addr(c, it) + c.wg * 8192, b = stage_addr(c, it) + 16384 + HALF * 16384;
  uint64_t da = make_desc(a, 16, 1024), db = make_desc(b, 8192, 1024);
#pragma unroll
  for (int kk = 0; kk < 4; kk++) wgmma_ss_n128<1>(acc, da + kk * 2, db + kk * 128, kk == 0 ? first_scale : 1);
}
__device__ __forceinline__ void stg_acquire(const Ctx& c, uint32_t sc) { mbar_wait(c.bars + 96 + c.wg * 16 + (sc & 1) * 8, ((sc >> 1) & 1) ^ 1); }
__device__ __forceinline__ void stg_commit(const Ctx& c, uint32_t sc) {
  fence_async_smem();
  __syncwarp();
  if ((c.t & 31) == 0) mbar_arrive(c.bars + 64 + c.wg * 16 + (sc & 1) * 8);
}
template <int OFF>
__device__ __forceinline__ void box_write(const Ctx& c, uint32_t base, const uint32_t (&t)[64]) {
#pragma unroll
  for (int kk = 0; kk < 4; kk++)
    stmatrix_x4(base + c.st_off + (((kk * 2) ^ c.st_sw) << 4), t[OFF + 4 * kk], t[OFF + 4 * kk + 1], t[OFF + 4 * kk + 2], t[OFF + 4 * kk + 3]);
}
__device__ __forceinline__ void acc_write(const Ctx& c, uint32_t base, const float (&s)[64]) {
#pragma unroll
  for (int kk = 0; kk < 8; kk++)
    stmatrix_x4(base + (kk >> 2) * 8192 + c.st_off + ((((kk & 3) * 2) ^ c.st_sw) << 4), pack_bf16(s[8 * kk], s[8 * kk + 1]),
                pack_bf16(s[8 * kk + 2], s[8 * kk + 3]), pack_bf16(s[8 * kk + 4], s[8 * kk + 5]), pack_bf16(s[8 * kk + 6], s[8 * kk + 7]));
}
__device__ __forceinline__ void half_store(Ctx& c, uint32_t (&t)[64]) {
  stg_acquire(c, c.sc);
  stg_acquire(c, c.sc + 1);
  box_write<0>(c, c.stg, t);
  box_write<16>(c, c.stg + 8192, t);
  fence_async_smem();
  __syncwarp();
  if ((c.t & 31) == 0) { mbar_arrive(c.bars + 64 + c.wg * 16); mbar_arrive(c.bars + 72 + c.wg * 16); }
  c.sc += 2;
#pragma unroll
  for (int i = 0; i < 32; i++) asm volatile("mov.b32 %0, %1;" : "=r"(t[i]) : "r"(t[i + 32]));
}
__device__ __forceinline__ void direct_store(const Ctx& c, const CUtensorMap* m, uint32_t a0, uint32_t a1, int col, int row) {
  fence_async_smem();
  bar_sync(3 + c.wg, 128);
  if (c.t == 0) {
    tma_store_2d(m, a0, col, row);
    tma_store_2d(m, a1, col + 64, row);
    asm volatile("cp.async.bulk.commit_group;" ::: "memory");
  }
}
template <int HALF>
__device__ __forceinline__ void final_half(const Ctx& c, const float (&acc)[64], const uint32_t (&t)[64], uint32_t e0, const CUtensorMap* m, int col, int row) {
  if (HALF == 0) wait_full(c, e0);
  wait_full(c, e0 + 1 + HALF);
  uint32_t ax[2];
#pragma unroll
  for (int q = 0; q < 2; q++) {
    const int bx = HALF * 2 + q, bo = bx + 4;
    ax[q] = stage_addr(c, e0 + bx / 3) + (bx % 3) * 16384 + c.wg * 8192;
    const uint32_t ao = stage_addr(c, e0 + bo / 3) + (bo % 3) * 16384 + c.wg * 8192 + c.st_off;
#pragma unroll
    for (int k4 = 0; k4 < 4; k4++) {
      uint32_t xv[4], ov[4];
      const uint32_t sw = ((k4 * 2) ^ c.st_sw) << 4;
      ldmatrix_x4(ax[q] + c.st_off + sw, xv[0], xv[1], xv[2], xv[3]);
      ldmatrix_x4(ao + sw, ov[0], ov[1], ov[2], ov[3]);
#pragma unroll
      for (int j = 0; j < 4; j++) {
        const int i = (q * 4 + k4) * 4 + j;
        xv[j] = fma_bf2(pack_bf16(acc[2 * i] + bf_lo(ov[j]), acc[2 * i + 1] + bf_hi(ov[j])), t[HALF * 32 + i], xv[j]);
      }
      stmatrix_x4(ax[q] + c.st_off + sw, xv[0], xv[1], xv[2], xv[3]);
    }
  }
  direct_store(c, m, ax[0], ax[1], col + HALF * 128, row);
}
__device__ __forceinline__ void rotate16(uint32_t (&t)[64]) {
#pragma unroll
  for (int i = 0; i < 16; i++)
    asm volatile("{\n.reg .b32 v;\nmov.b32 v, %0;\nmov.b32 %0, %1;\nmov.b32 %1, %2;\nmov.b32 %2, %3;\nmov.b32 %3, v;\n}\n"
                 : "+r"(t[i]), "+r"(t[i + 16]), "+r"(t[i + 32]), "+r"(t[i + 48]));
}
__device__ __forceinline__ float quad_rcp_sum(float l) {
  l += __shfl_xor_sync(0xffffffffu, l, 1);
  l += __shfl_xor_sync(0xffffffffu, l, 2);
  float r; asm("rcp.approx.ftz.f32 %0, %1;" : "=f"(r) : "f"(l));
  return r;
}
template <int OFF>
__device__ __forceinline__ void capture_plain(uint32_t (&d)[64], const float (&s)[64]) {
#pragma unroll
  for (int i = 0; i < 32; i++) d[OFF + i] = pack_bf16(s[2 * i], s[2 * i + 1]);
}
template <int OFF>
__device__ __forceinline__ void capture_scaled(uint32_t (&d)[64], const float (&s)[64], float r0, float r1) {
#pragma unroll
  for (int i = 0; i < 32; i++) { const float r = (i & 1) ? r1 : r0; d[OFF + i] = pack_bf16(s[2 * i] * r, s[2 * i + 1] * r); }
}
template <int OFF>
__device__ __forceinline__ void capture_gate(uint32_t (&d)[64], const float (&s)[64], float b0, float b1) {
#pragma unroll
  for (int i = 0; i < 32; i++) {
    const float b = (i & 1) ? b1 : b0;
    d[OFF + i] = mul_bf2(pack_bf16(fmaf(s[2 * i], 0.5f, b), fmaf(s[2 * i + 1], 0.5f, b)), d[OFF + i]);
  }
}
__device__ __forceinline__ void issue_qk(const Ctx& c, float (&s)[64], uint32_t qaddr, uint32_t it) {
  uint64_t da = make_desc(qaddr, 16, 1024), db = make_desc(stage_addr(c, it), 16, 1024);
#pragma unroll
  for (int kk = 0; kk < 8; kk++) wgmma_ss_n128<0>(s, da + (kk >> 2) * 512 + (kk & 3) * 2, db + (kk >> 2) * 1024 + (kk & 3) * 2, kk == 0 ? 0 : 1);
}
__device__ __forceinline__ void issue_pv(const Ctx& c, float (&o)[64], uint32_t paddr, uint32_t it, int first_scale) {
  uint64_t da = make_desc(paddr, 16, 1024), db = make_desc(stage_addr(c, it), 16384, 1024);
#pragma unroll
  for (int kk = 0; kk < 8; kk++) wgmma_ss_n128<1>(o, da + (kk >> 2) * 512 + (kk & 3) * 2, db + kk * 128, kk == 0 ? first_scale : 1);
}
template <int I0, int I1>
__device__ __forceinline__ void exp_part(float (&x)[64], float& l0, float& l1) {
#pragma unroll
  for (int i = I0; i < I1; i += 4) {
    x[i] = ex2(x[i]); x[i + 1] = ex2(x[i + 1]); x[i + 2] = ex2(x[i + 2]); x[i + 3] = ex2(x[i + 3]);
    l0 += x[i] + x[i + 1]; l1 += x[i + 2] + x[i + 3];
  }
}
template <int K0, int K1>
__device__ __forceinline__ void part_write(const Ctx& c, uint32_t base, const float (&s)[64]) {
#pragma unroll
  for (int kk = K0; kk < K1; kk++)
    stmatrix_x4(base + (kk >> 2) * 8192 + c.st_off + ((((kk & 3) * 2) ^ c.st_sw) << 4), pack_bf16(s[8 * kk], s[8 * kk + 1]),
                pack_bf16(s[8 * kk + 2], s[8 * kk + 3]), pack_bf16(s[8 * kk + 4], s[8 * kk + 5]), pack_bf16(s[8 * kk + 6], s[8 * kk + 7]));
}
#define EXP_A 16
#define EXP_B 40
constexpr float SM_SCALE = 0.08838834764831845f * 1.4426950408889634f;
__device__ __forceinline__ void row_max(const float (&s)[64], float& x0, float& x1) {
  float p[4], q[4];
#pragma unroll
  for (int k = 0; k < 4; k++) { p[k] = fmaxf(s[4 * k], s[4 * k + 1]); q[k] = fmaxf(s[4 * k + 2], s[4 * k + 3]); }
#pragma unroll
  for (int j = 4; j < 16; j++) {
    p[j & 3] = fmaxf(p[j & 3], fmaxf(s[4 * j], s[4 * j + 1]));
    q[j & 3] = fmaxf(q[j & 3], fmaxf(s[4 * j + 2], s[4 * j + 3]));
  }
  x0 = fmaxf(x0, fmaxf(fmaxf(p[0], p[1]), fmaxf(p[2], p[3])));
  x1 = fmaxf(x1, fmaxf(fmaxf(q[0], q[1]), fmaxf(q[2], q[3])));
  x0 = fmaxf(x0, __shfl_xor_sync(0xffffffffu, x0, 1));
  x1 = fmaxf(x1, __shfl_xor_sync(0xffffffffu, x1, 1));
  x0 = fmaxf(x0, __shfl_xor_sync(0xffffffffu, x0, 2));
  x1 = fmaxf(x1, __shfl_xor_sync(0xffffffffu, x1, 2));
}
__device__ __forceinline__ float warp_sum(float v) {
#pragma unroll
  for (int o = 16; o > 0; o >>= 1) v += __shfl_xor_sync(0xffffffffu, v, o);
  return v;
}
template <int NV>
__device__ __forceinline__ void ln_row(uint4 (&v)[NV]) {
  float s = 0.f;
#pragma unroll
  for (int i = 0; i < NV; i++)
    s += (bf_lo(v[i].x) + bf_hi(v[i].x)) + (bf_lo(v[i].y) + bf_hi(v[i].y)) + (bf_lo(v[i].z) + bf_hi(v[i].z)) + (bf_lo(v[i].w) + bf_hi(v[i].w));
  float mean = warp_sum(s) * (1.0f / (NV * 256));
  float q = 0.f;
#pragma unroll
  for (int i = 0; i < NV; i++) {
    const uint32_t w[4] = {v[i].x, v[i].y, v[i].z, v[i].w};
#pragma unroll
    for (int j = 0; j < 4; j++) {
      float a = bf_lo(w[j]) - mean, b = bf_hi(w[j]) - mean;
      q = fmaf(a, a, q); q = fmaf(b, b, q);
    }
  }
  float rstd = rsqrtf(warp_sum(q) * (1.0f / (NV * 256)) + 1e-5f);
#pragma unroll
  for (int i = 0; i < NV; i++) {
    v[i].x = pack_bf16((bf_lo(v[i].x) - mean) * rstd, (bf_hi(v[i].x) - mean) * rstd);
    v[i].y = pack_bf16((bf_lo(v[i].y) - mean) * rstd, (bf_hi(v[i].y) - mean) * rstd);
    v[i].z = pack_bf16((bf_lo(v[i].z) - mean) * rstd, (bf_hi(v[i].z) - mean) * rstd);
    v[i].w = pack_bf16((bf_lo(v[i].w) - mean) * rstd, (bf_hi(v[i].w) - mean) * rstd);
  }
}

#define PROF(slot)
#define PROFT(slot, thr)
#define PROFG(slot)

struct Prod {
  uint32_t sbase, bars, it, rank, lane, epoch;
};
__device__ __forceinline__ uint32_t prod_acquire(Prod& p, uint32_t bytes) {
  uint32_t s = p.it & 3;
  mbar_wait(p.bars + 32 + 8 * s, ((p.it >> 2) & 1) ^ 1);
  if (p.lane == 0) mbar_expect_tx(p.bars + 8 * s, bytes);
  p.it++;
  return s;
}
__device__ __forceinline__ void dep_wait(const Prod& p, uint32_t& ready, int base, int n, uint32_t target, int i) {
  if ((ready >> i) & 1) return;
  uint32_t spins = 0;
  do {
    const bool ok = (int)p.lane < n && (int)(ld_relaxed(&g_flags[base + p.lane]) - target * p.epoch) >= 0;
    ready = __ballot_sync(0xffffffffu, ok);
    if (++spins > (1u << 22)) __trap();
  } while (!((ready >> i) & 1));
  fence_acquire();
  __syncwarp();
  fence_async();
}
__device__ __forceinline__ void prod_gemm(Prod& p, const CUtensorMap* mA, int arow, const CUtensorMap* mB, int chunk, int k0, int k1,
                                          int base, int n, uint32_t target, int shift) {
  uint32_t ready = 0;
#pragma unroll 1
  for (int k = k0; k < k1; k++) {
    dep_wait(p, ready, base, n, target, k >> shift);
    uint32_t s = prod_acquire(p, STAGE_BYTES);
    uint32_t a = p.sbase + s * STAGE_BYTES;
    if (p.lane == 0) {
      tma_load_3d_mc(a + 16384 + p.rank * 16384, mB, p.bars + 8 * s, k * 64, chunk + p.rank * 2);
      tma_load_2d(a, mA, p.bars + 8 * s, k * 64, arow);
    }
  }
}

__global__ void __cluster_dims__(2, 1, 1) __launch_bounds__(384, 1) mega_kernel(const __grid_constant__ Params P) {
  extern __shared__ uint8_t smem_raw[];
  const uint32_t sbase = (smem_u32(smem_raw) + 1023) & ~1023u;
  const uint32_t bars = sbase + SM_BAR;
  const int tid = threadIdx.x, lane = tid & 31;
  const int warp = __shfl_sync(0xffffffffu, tid >> 5, 0), wg = warp >> 2;
  const uint32_t rank = blockIdx.x & 1;
  const int cid = blockIdx.x >> 1;
  uint4 v0[4], v1[4];
  if (wg < 2 && blockIdx.x < 128) {
    const uint4* xr = reinterpret_cast<const uint4*>(P.x + (size_t)(blockIdx.x * 16 + warp * 2) * DM);
#pragma unroll
    for (int i = 0; i < 4; i++) { v0[i] = __ldg(xr + i * 32 + lane); v1[i] = __ldg(xr + 128 + i * 32 + lane); }
  }
  PROFG(60); PROF(61);

  if (tid == 256) {
    for (int s = 0; s < STAGES; s++) { mbar_init(bars + 8 * s, 1); mbar_init(bars + 32 + 8 * s, 4); }
    for (int w = 0; w < 4; w++) { mbar_init(bars + 64 + 8 * w, 4); mbar_init(bars + 96 + 8 * w, 1); }
    for (int w = 0; w < 2; w++) { mbar_init(bars + 128 + 8 * w, 4); mbar_init(bars + 144 + 8 * w, 1); }
    asm volatile("fence.mbarrier_init.release.cluster;" ::: "memory");
  }
  uint32_t epoch = 0;
  if (lane == 0 && (warp == 8 || warp == 11)) epoch = atomicAdd(&g_flags[F_TICKET], 1) / (2 * gridDim.x) + 1;
  __syncwarp();
  cluster_arrive_relaxed();

  if (wg == 2) {
    asm volatile("setmaxnreg.dec.sync.aligned.u32 40;");
    cluster_wait();
    if (warp == 8) {
      Prod p{sbase, bars, 0, rank, (uint32_t)lane, __shfl_sync(0xffffffffu, epoch, 0)};
#pragma unroll 1
      for (int ti = 0; ti < MAXT; ti++) {
        const uint32_t task = P.tasks[cid][ti];
        const int type = task & 7, mb = ((task >> 4) & 15) * 2 + rank, idx = task >> 8;
        if (type == T_NONE) break;
        const int arow = mb * 128;
        int mA = M_XN, mB = M_WIN, chunk = idx * 4, nk = 16, base = F_XN + mb, n = 1, shift = 5;
        uint32_t target = 64;
        int k0 = 0;
        if (type == T_Z2) chunk += FH / 64;
        else if (type == T_QA) mB = M_WQ;
        else if (type == T_G) { mA = M_WSP; mB = M_Z2; nk = 32; base = F_Z2N; n = 16; target = 14; shift = 1; }
        else if (type == T_SP || type == T_SF) { mA = M_O_LD; mB = M_WO; k0 = P.krange[cid][0]; nk = P.krange[cid][1]; base = F_O + mb * 32; n = 32; target = 2; shift = 1; }
        else if (type == T_Y) { mA = M_H_LD; mB = M_WOUT; nk = 28; base = F_H + mb * 8; n = 7; target = 2; shift = 2; }
        if (ti == 0) {
          for (int k = 0; k < STAGES; k++) {
            prod_acquire(p, STAGE_BYTES);
            if (lane == 0) tma_load_3d_mc(sbase + k * STAGE_BYTES + 16384 + rank * 16384, &P.maps[mB], bars + 8 * k, k * 64, chunk + rank * 2);
          }
          uint32_t ready = 0;
          dep_wait(p, ready, base, 1, target, 0);
          if (lane == 0)
            for (int k = 0; k < STAGES; k++) tma_load_2d(sbase + k * STAGE_BYTES, &P.maps[M_XN], bars + 8 * k, k * 64, arow);
          k0 = STAGES;
        }
        prod_gemm(p, &P.maps[mA], arow, &P.maps[mB], chunk, k0, nk, base, n, target, shift);
        if (type == T_QA) {
          const int kvrow = (idx >> 2) * SK + (SK - WIN);
#pragma unroll 1
          for (int j = 0; j < 16; j++) {
            const bool isK = (j == 0) || ((j & 1) && j != 15);
            const int ch = isK ? ((j + 1) >> 1) & 3 : (j == 15 ? 3 : ((j >> 1) - 1) & 3);
            uint32_t s = prod_acquire(p, 32768);
            if (lane == 0) tma_load_2d_mc(sbase + s * STAGE_BYTES + rank * 16384, &P.maps[isK ? M_K : M_V], bars + 8 * s, rank * 64, kvrow + ch * 128);
          }
        }
        if (type == T_SF) {
          uint32_t ready = 0, s = 0;
#pragma unroll 1
          for (int b = 0; b < 8; b++) {
            if (b % 3 == 0) s = prod_acquire(p, b == 6 ? 32768 : 49152);
            if (b == 4) dep_wait(p, ready, F_SY + mb * 4 + idx, 1, 2, 0);
            if (lane == 0) tma_load_2d(sbase + s * STAGE_BYTES + (b % 3) * 16384, &P.maps[b < 4 ? M_X : M_SY_LD], bars + 8 * s, idx * 256 + (b & 3) * 64, arow);
          }
        }
      }
    } else if (warp == 9 || warp == 10) {
      if (lane == 0) {
        const int w = warp - 9;
        uint32_t sc = 0;
#pragma unroll 1
        for (int ti = 0; ti < MAXT; ti++) {
          const uint32_t task = P.tasks[cid][ti];
          const int type = task & 7, mb = ((task >> 4) & 15) * 2 + rank, idx = task >> 8;
          if (type == T_NONE) break;
          if (type == T_Z1 || type >= T_SP) continue;
          const int mi = type == T_Z2 ? M_Z2_ST : type == T_QA ? M_O_ST : M_H_ST;
          const int f = type == T_Z2 ? F_Z2N + mb : type == T_QA ? F_O + mb * 32 + idx * 2 : F_H + mb * 8 + idx;
#pragma unroll 1
          for (int q = 0; q < 4; q++, sc++) {
            mbar_wait(bars + 64 + w * 16 + (sc & 1) * 8, (sc >> 1) & 1);
            tma_store_2d(&P.maps[mi], sbase + SM_STG + w * 16384 + (sc & 1) * 8192, idx * 256 + q * 64, mb * 128 + w * 64);
            asm volatile("cp.async.bulk.commit_group;" ::: "memory");
            asm volatile("cp.async.bulk.wait_group.read 0;" ::: "memory");
            mbar_arrive(bars + 96 + w * 16 + (sc & 1) * 8);
            if (q == 3 || (q == 1 && type == T_QA)) {
              asm volatile("cp.async.bulk.wait_group 0;" ::: "memory");
              red_release(&g_flags[f + (type == T_QA ? q >> 1 : 0)]);
            }
          }
        }
      }
    } else {
      const uint32_t task = P.tasks[cid][0];
      epoch = __shfl_sync(0xffffffffu, epoch, 0);
      if ((task & 7) == T_Z2) {
        const int mb = ((task >> 4) & 15) * 2 + rank, idx = task >> 8;
        const uint32_t st = sbase + SM_STAT + lane * 16;
#pragma unroll 1
        for (int w = 0; w < 2; w++) {
          float4 v;
          mbar_wait(bars + 128 + 8 * w, 0);
          asm volatile("ld.shared.v4.f32 {%0, %1, %2, %3}, [%4];" : "=f"(v.x), "=f"(v.y), "=f"(v.z), "=f"(v.w) : "r"(st + w * 512) : "memory");
          *reinterpret_cast<float4*>(&g_stats[idx * SEQ + mb * 128 + w * 64 + lane * 2]) = v;
          __syncwarp();
          if (lane == 0) red_release(&g_flags[F_ST + mb * 2 + w]);
        }
#pragma unroll 1
        for (int w = 0; w < 2; w++) {
          flag_wait(F_ST + mb * 2 + w, 7 * epoch);
          float4 a = make_float4(0.f, 0.f, 0.f, 0.f);
#pragma unroll
          for (int i = 0; i < 7; i++) {
            const float4 v = __ldcg(reinterpret_cast<const float4*>(&g_stats[i * SEQ + mb * 128 + w * 64 + lane * 2]));
            a.x += v.x; a.y += v.y; a.z += v.z; a.w += v.w;
          }
          const float m0 = a.x * (1.0f / FH), m1 = a.z * (1.0f / FH);
          const float q0 = rsqrtf(fmaxf(fmaf(-m0, m0, a.y * (1.0f / FH)), 0.f) + 4e-5f);
          const float q1 = rsqrtf(fmaxf(fmaf(-m1, m1, a.w * (1.0f / FH)), 0.f) + 4e-5f);
          asm volatile("st.shared.v4.b32 [%0], {%1, %2, %3, %4};" ::"r"(st + w * 512), "r"(pack_bf16(q0, q0)), "r"(pack_bf16(-m0 * q0, -m0 * q0)),
                       "r"(pack_bf16(q1, q1)), "r"(pack_bf16(-m1 * q1, -m1 * q1)) : "memory");
          __syncwarp();
          if (lane == 0) mbar_arrive(bars + 144 + 8 * w);
        }
      }
    }
  } else {
    asm volatile("setmaxnreg.inc.sync.aligned.u32 232;");
    if (blockIdx.x < 128) {
      const int r0 = blockIdx.x * 16 + warp * 2;
      ln_row<4>(v0);
      ln_row<4>(v1);
      uint4* xo = reinterpret_cast<uint4*>(g_xn + (size_t)r0 * DM);
#pragma unroll
      for (int i = 0; i < 4; i++) { xo[i * 32 + lane] = v0[i]; xo[128 + i * 32 + lane] = v1[i]; }
      __syncwarp();
      if (lane == 0) red_release(&g_flags[F_XN + (blockIdx.x >> 3)]);
    }
    cluster_wait();
    PROF(62);

    Ctx c;
    c.sbase = sbase; c.bars = bars; c.it = 0; c.sc = 0; c.wg = wg; c.t = tid & 127;
    c.stg = sbase + SM_STG + wg * 16384;
    {
      const int row = (warp & 3) * 16 + ((lane >> 3) & 1) * 8 + (lane & 7);
      c.st_off = row * 128;
      c.st_sw = (lane >> 4) ^ (lane & 7);
    }
    if (wg == 1) bar_arrive(1, 256);
    float accA[64], accB[64];
    uint32_t t[64];
    int pend = 0, ptype = 0;
    float s0 = 0.f, s1 = 0.f, q0 = 0.f, q1 = 0.f;
    wait_full(c, 0);
    wgmma_fence();
    mma_half<0>(c, accA, 0, 0);
    mma_half<1>(c, accB, 0, 0);
    wgmma_commit();
    uint32_t task = P.tasks[cid][0];

#pragma unroll 1
    for (int ti = 0;; ti++) {
      const int type = task & 7, mb = ((task >> 4) & 15) * 2 + rank;
      const uint32_t next = P.tasks[cid][ti + 1];
      const bool is_qa = type == T_QA;
      PROF(ti * 4);
      uint32_t it = c.it + 1;
      const uint32_t nk = type == T_G ? 32 : type == T_Y ? 28 : (type == T_SP || type == T_SF) ? P.krange[cid][1] - P.krange[cid][0] : 16;
      const uint32_t last = c.it + nk - 1;
      const uint32_t smask = nk >= 20 ? 3 : 1, sphase = c.it + 1 + (wg ? (smask + 1) >> 1 : 0);
#pragma unroll 1
      for (; it < last; it++) {
        wait_full(c, it);
        wgmma_fence();
        mma_half<0>(c, accA, it, 1);
        mma_half<1>(c, accB, it, 1);
        wgmma_commit();
        wgmma_wait<1>();
        release(c, it - 1);
        if (pend > 0 && ((it - sphase) & smask) == 0) {
          const uint32_t stat = sbase + SM_STAT + (wg * 64 + (warp & 3) * 16 + (lane >> 2)) * 8;
          if (pend > 3) {
            if (ptype == T_Z1) {
#pragma unroll
              for (int i = 0; i < 16; i++) t[i] = pack_bf16(gelu2_tanh(bf_lo(t[i])), gelu2_tanh(bf_hi(t[i])));
            } else if (ptype == T_Y) {
#pragma unroll
              for (int i = 0; i < 16; i++) t[i] = pack_bf16(silu(bf_lo(t[i])), silu(bf_hi(t[i])));
            } else {
#pragma unroll
              for (int i = 0; i < 16; i++) {
                const float a = gelu2_tanh(bf_lo(t[i])), b = gelu2_tanh(bf_hi(t[i]));
                t[i] = pack_bf16(a, b);
                if (i & 1) { s1 += a + b; q1 = fmaf(a, a, fmaf(b, b, q1)); }
                else { s0 += a + b; q0 = fmaf(a, a, fmaf(b, b, q0)); }
              }
            }
            rotate16(t);
            if (pend == 4) {
              if (ptype != T_Z2) pend = 1;
              else {
#pragma unroll
                for (int o = 1; o < 4; o <<= 1) {
                  s0 += __shfl_xor_sync(0xffffffffu, s0, o); q0 += __shfl_xor_sync(0xffffffffu, q0, o);
                  s1 += __shfl_xor_sync(0xffffffffu, s1, o); q1 += __shfl_xor_sync(0xffffffffu, q1, o);
                }
                if ((lane & 3) == 0) {
                  asm volatile("st.shared.v2.f32 [%0], {%1, %2};" ::"r"(stat), "f"(s0), "f"(q0) : "memory");
                  asm volatile("st.shared.v2.f32 [%0], {%1, %2};" ::"r"(stat + 64), "f"(s1), "f"(q1) : "memory");
                }
                __syncwarp();
                if (lane == 0) mbar_arrive(bars + 128 + 8 * wg);
              }
            }
          } else if (pend < 3) {
            if (ptype == T_Z2) {
              uint32_t a0, b0, a1, b1;
              mbar_wait(bars + 144 + 8 * wg, 0);
              asm volatile("ld.shared.v2.b32 {%0, %1}, [%2];" : "=r"(a0), "=r"(b0) : "r"(stat) : "memory");
              asm volatile("ld.shared.v2.b32 {%0, %1}, [%2];" : "=r"(a1), "=r"(b1) : "r"(stat + 64) : "memory");
#pragma unroll
              for (int i = 0; i < 32; i++) t[i] = fma_bf2(t[i], (i & 1) ? a1 : a0, (i & 1) ? b1 : b0);
            }
            half_store(c, t);
          }
          pend--;
        }
      }
      float r0, r1;
      {
        const int brow = mb * 128 + wg * 64 + (warp & 3) * 16 + (lane >> 2);
        r0 = 0.5f * __bfloat162float(P.b_sp[brow]); r1 = 0.5f * __bfloat162float(P.b_sp[brow + 8]);
      }
      wait_full(c, it);
      wgmma_fence();
      mma_half<0>(c, accA, it, 1);
      wgmma_commit();
      mma_half<1>(c, accB, it, 1);
      wgmma_commit();
      wgmma_wait<1>();
      release(c, it - 1);
      it++;
      PROF(ti * 4 + 1);
      if (type == T_SF || type == T_SP) {
        const int col = (task >> 8) * 256, row = mb * 128 + wg * 64;
        if (type == T_SF) {
          final_half<0>(c, accA, t, it, &P.maps[M_OUT], col, row);
          wgmma_wait<0>();
          final_half<1>(c, accB, t, it, &P.maps[M_OUT], col, row);
        } else {
          const uint32_t a0 = stage_addr(c, it) + wg * 8192, a1 = stage_addr(c, it + 1) + wg * 8192;
          const uint32_t a2 = stage_addr(c, it + 2) + wg * 8192, a3 = stage_addr(c, it + 3) + wg * 8192;
          part_write<0, 4>(c, a0, accA);
          part_write<4, 8>(c, a1 - 8192, accA);
          direct_store(c, &P.maps[M_SY_ST], a0, a1, col, row);
          wgmma_wait<0>();
          part_write<0, 4>(c, a2, accB);
          part_write<4, 8>(c, a3 - 8192, accB);
          direct_store(c, &P.maps[M_SY_ST], a2, a3, col + 128, row);
        }
        if (c.t == 0) {
          if (type == T_SP) {
            asm volatile("cp.async.bulk.wait_group 0;" ::: "memory");
            red_release(&g_flags[F_SY + mb * 4 + (task >> 8)]);
          } else {
            asm volatile("cp.async.bulk.wait_group.read 0;" ::: "memory");
          }
        }
        pend = 0;
        PROF(ti * 4 + 2);
        break;
      }
      if (is_qa) {
        stg_acquire(c, c.sc);
        stg_acquire(c, c.sc + 1);
        acc_write(c, c.stg, accA);
        fence_async_smem();
        bar_sync(3 + wg, 128);
        const uint32_t qb = stage_addr(c, it + 2 + wg) + 32768;
        uint32_t pb = stage_addr(c, it + wg) + 32768;
        wait_full(c, it);
        wgmma_fence();
        issue_qk(c, accA, c.stg, it);
        wgmma_commit();
        wgmma_wait<0>();
        release(c, it - 1);
        release(c, it);
        float n0, n1, l0 = 0.f, l1 = 0.f;
        float x[64];
        bool rescale = false;
        {
          float x0 = -INFINITY, x1 = -INFINITY;
          row_max(accA, x0, x1);
          n0 = -x0 * SM_SCALE; n1 = -x1 * SM_SCALE;
#pragma unroll
          for (int i = 0; i < 64; i++) x[i] = fmaf(accA[i], SM_SCALE, (i & 2) ? n1 : n0);
        }
#pragma unroll 1
        for (int j = 0;; j++) {
          fence_async_smem();
          if (j == 5) {
            __syncwarp();
            if (lane == 0) { mbar_arrive(bars + 64 + wg * 16); mbar_arrive(bars + 72 + wg * 16); }
            c.sc += 2;
          }
          bar_sync(1 + wg, 256);
          if (j > 0) {
            it++;
            wait_full(c, it);
            wgmma_fence();
            issue_pv(c, accB, pb, it, (j - 1) & 3);
            wgmma_commit();
          }
          exp_part<0, EXP_A>(x, l0, l1);
          if (j == 6) { stg_acquire(c, c.sc); stg_acquire(c, c.sc + 1); pb = c.stg; }
          if (j < 7) {
            wait_full(c, it + 1);
            wgmma_fence();
            issue_qk(c, accA, j < 3 ? c.stg : qb, it + 1);
            wgmma_commit();
            bar_arrive(2 - wg, 256);
            wgmma_wait<1>();
          } else {
            bar_arrive(2 - wg, 256);
            wgmma_wait<0>();
          }
          if (j > 0) release(c, it);
          exp_part<EXP_A, EXP_B>(x, l0, l1);
          part_write<0, EXP_B / 8>(c, pb, x);
          wgmma_wait<0>();
          if (j < 7) { it++; release(c, it); }
          if (j == 3) {
            float x0 = -INFINITY, x1 = -INFINITY;
            row_max(accA, x0, x1);
            n0 = -x0 * SM_SCALE; n1 = -x1 * SM_SCALE;
          }
          if (rescale) {
#pragma unroll
            for (int i = 0; i < 16; i++) { accB[4 * i] *= r0; accB[4 * i + 1] *= r0; accB[4 * i + 2] *= r1; accB[4 * i + 3] *= r1; }
            rescale = false;
          }
          if ((j & 3) == 0) {
            if (j == 0) wait_full(c, it + 1 + wg);
            acc_write(c, j == 0 ? qb : c.stg, accB);
          }
          int top[4] = {0, 0, 0, 0};
          auto next_arg = [&](int i) {
            const float nn = (i & 2) ? n1 : n0;
            asm volatile("fma.rn.f32 %0, %1, %2, %3;" : "=f"(x[i]) : "f"(accA[i]), "f"(SM_SCALE), "f"(nn));
            asm volatile("fma.rn.f32 %0, %1, %2, %3;" : "=f"(x[i + 1]) : "f"(accA[i + 1]), "f"(SM_SCALE), "f"(nn));
            top[(i >> 1) & 3] = __vimax3_s32(top[(i >> 1) & 3], __float_as_int(x[i]), __float_as_int(x[i + 1]));
          };
#pragma unroll
          for (int kk = EXP_B / 8; kk < 8; kk++) {
#pragma unroll
            for (int i = 8 * kk; i < 8 * kk + 8; i++) {
              asm volatile("ex2.approx.ftz.f32 %0, %0;" : "+f"(x[i]));
              const int a = 2 * (i - EXP_B);
              if (a < 8 * kk) next_arg(a);
            }
            l0 += (x[8 * kk] + x[8 * kk + 1]) + (x[8 * kk + 4] + x[8 * kk + 5]);
            l1 += (x[8 * kk + 2] + x[8 * kk + 3]) + (x[8 * kk + 6] + x[8 * kk + 7]);
            stmatrix_x4(pb + (kk >> 2) * 8192 + c.st_off + ((((kk & 3) * 2) ^ c.st_sw) << 4), pack_bf16(x[8 * kk], x[8 * kk + 1]),
                        pack_bf16(x[8 * kk + 2], x[8 * kk + 3]), pack_bf16(x[8 * kk + 4], x[8 * kk + 5]), pack_bf16(x[8 * kk + 6], x[8 * kk + 7]));
          }
#pragma unroll
          for (int a = 2 * (64 - EXP_B); a < 64; a += 2) next_arg(a);
          const bool over = __any_sync(0xffffffffu, max(max(top[0], top[1]), max(top[2], top[3])) > 0x41800000);
          if (j == 7) break;
          if (j == 3) {
            r0 = quad_rcp_sum(l0); r1 = quad_rcp_sum(l1);
            l0 = 0.f; l1 = 0.f;
            rescale = true;
          } else if (over) {
            float d0 = __int_as_float(max(top[0], top[2])), d1 = __int_as_float(max(top[1], top[3]));
            d0 = fmaxf(d0, __shfl_xor_sync(0xffffffffu, d0, 1)); d1 = fmaxf(d1, __shfl_xor_sync(0xffffffffu, d1, 1));
            d0 = fmaxf(d0, __shfl_xor_sync(0xffffffffu, d0, 2)); d1 = fmaxf(d1, __shfl_xor_sync(0xffffffffu, d1, 2));
#pragma unroll
            for (int i = 0; i < 64; i++) x[i] -= (i & 2) ? d1 : d0;
            n0 -= d0; n1 -= d1;
            r0 = ex2(-d0); r1 = ex2(-d1);
            l0 *= r0; l1 *= r1;
            rescale = true;
          }
        }
        fence_async_smem();
        bar_sync(1 + wg, 256);
        wait_full(c, it + 1);
        wgmma_fence();
        issue_pv(c, accB, pb, it + 1, 1);
        wgmma_commit();
        it += 2;
        r0 = quad_rcp_sum(l0); r1 = quad_rcp_sum(l1);
#pragma unroll
        for (int i = 0; i < 64; i++) t[i] = 0;
      } else if (type == T_G) {
        capture_gate<0>(t, accA, r0, r1);
      } else {
        capture_plain<0>(t, accA);
      }
      if (next) wait_full(c, it);
      wgmma_fence();
      mma_half<0>(c, accA, it, 0);
      wgmma_commit();
      if (is_qa) bar_arrive(2 - wg, 256);
      wgmma_wait<1>();
      c.it = it;
      release(c, it - 1);
      if (type == T_G) capture_gate<32>(t, accB, r0, r1);
      else if (is_qa) capture_scaled<0>(t, accB, r0, r1);
      else capture_plain<32>(t, accB);
      wgmma_fence();
      mma_half<1>(c, accB, it, 0);
      wgmma_commit();
      pend = is_qa ? 1 : (type == T_Z2 || type == T_Z1 || type == T_Y) ? 7 : 2;
      ptype = type;
      PROF(ti * 4 + 2);
      PROF(ti * 4 + 3);
      if (!next) break;
      task = next;
    }
#pragma unroll 1
    for (; pend > 0; pend--) half_store(c, t);
    wgmma_wait<0>();
    PROF(59);
  }
  __syncwarp();
  cluster_arrive_relaxed();
  cluster_wait();
  PROFG(63);
}

typedef CUresult (*PFN_encodeTiled)(CUtensorMap*, CUtensorMapDataType, cuuint32_t, void*, const cuuint64_t*, const cuuint64_t*, const cuuint32_t*,
                                    const cuuint32_t*, CUtensorMapInterleave, CUtensorMapSwizzle, CUtensorMapL2promotion, CUtensorMapFloatOOBfill);

static void map_2d(PFN_encodeTiled enc, CUtensorMap* m, const void* ptr, uint64_t rows, uint64_t cols, uint32_t box_rows = 128) {
  cuuint64_t dims[2] = {cols, rows}; cuuint64_t strides[1] = {cols * 2};
  cuuint32_t box[2] = {64, box_rows}; cuuint32_t es[2] = {1, 1};
  enc(m, CU_TENSOR_MAP_DATA_TYPE_BFLOAT16, 2, const_cast<void*>(ptr), dims, strides, box, es, CU_TENSOR_MAP_INTERLEAVE_NONE,
      CU_TENSOR_MAP_SWIZZLE_128B, CU_TENSOR_MAP_L2_PROMOTION_L2_256B, CU_TENSOR_MAP_FLOAT_OOB_FILL_NONE);
}
static void map_3d(PFN_encodeTiled enc, CUtensorMap* m, const void* ptr, uint64_t rows, uint64_t cols) {
  cuuint64_t dims[3] = {64, rows, cols / 64}; cuuint64_t strides[2] = {cols * 2, 128};
  cuuint32_t box[3] = {64, 64, 2}; cuuint32_t es[3] = {1, 1, 1};
  enc(m, CU_TENSOR_MAP_DATA_TYPE_BFLOAT16, 3, const_cast<void*>(ptr), dims, strides, box, es, CU_TENSOR_MAP_INTERLEAVE_NONE,
      CU_TENSOR_MAP_SWIZZLE_128B, CU_TENSOR_MAP_L2_PROMOTION_L2_256B, CU_TENSOR_MAP_FLOAT_OOB_FILL_NONE);
}
static unsigned short mk(int type, int mp, int idx) { return (unsigned short)(type | (mp << 4) | (idx << 8)); }

#define SPLIT0 54
#define SPLIT1 50
#define SPLIT2 50
#define SPLIT3 54
static void build_schedule(Params& P) {
  for (int c = 0; c < NCLUSTERS; c++)
    for (int t = 0; t <= MAXT; t++) P.tasks[c][t] = 0;
  static const char* const plan[8] = {
      "z0 q1 h2 q12",
      "q0 h1 q9",
      "z1 q2 h3 q13",
      "z2 q3 q7 q10",
      "z3 q4 h4 q14",
      "z4 q5 q8 q11",
      "z5 q6 h5 q15",
      "z6 h0 h6"
  };
  static const int split[4] = {SPLIT0, SPLIT1, SPLIT2, SPLIT3};
  for (int mp = 0; mp < 8; mp++) {
    for (int j = 0; j < 8; j++) {
      unsigned short* T = P.tasks[mp * 8 + j];
      int n = 0;
      for (const char* q = plan[j]; *q;) {
        const char kind = *q++;
        int idx = 0;
        while (*q >= '0' && *q <= '9') idx = idx * 10 + (*q++ - '0');
        while (*q == ' ') q++;
        if (kind == 'z') T[n++] = mk(T_Z2, mp, idx);
        else if (kind == 'q') T[n++] = mk(T_QA, mp, idx);
        else { T[n++] = mk(T_Z1, mp, idx); T[n++] = mk(T_G, mp, idx); }
      }
      if (j & 1) {
        T[n++] = mk(T_SP, mp, j >> 1);
        P.krange[mp * 8 + j][0] = 0; P.krange[mp * 8 + j][1] = (unsigned char)split[j >> 1];
      } else {
        T[n++] = mk(T_Y, mp, j >> 1); T[n++] = mk(T_SF, mp, j >> 1);
        P.krange[mp * 8 + j][0] = (unsigned char)split[j >> 1]; P.krange[mp * 8 + j][1] = 64;
      }
    }
  }
}

extern "C" void kernel_launch(void* const* d_in, const int* in_sizes, int n_in, void* d_out, int out_size) {
  (void)in_sizes; (void)n_in; (void)out_size;
  static PFN_encodeTiled enc = nullptr;
  static void *p_xn, *p_z2, *p_o, *p_h, *p_sy;
  if (!enc) {
    void* fn = nullptr; cudaDriverEntryPointQueryResult qr;
    cudaGetDriverEntryPoint("cuTensorMapEncodeTiled", &fn, cudaEnableDefault, &qr);
    enc = (PFN_encodeTiled)fn;
    cudaGetSymbolAddress(&p_xn, g_xn); cudaGetSymbolAddress(&p_z2, g_z2); cudaGetSymbolAddress(&p_o, g_o);
    cudaGetSymbolAddress(&p_h, g_h); cudaGetSymbolAddress(&p_sy, g_sy);
    cudaFuncSetAttribute(mega_kernel, cudaFuncAttributeMaxDynamicSharedMemorySize, SMEM_BYTES);
  }
  Params P;
  map_2d(enc, &P.maps[M_XN], p_xn, SEQ, DM);
  map_2d(enc, &P.maps[M_WSP], d_in[7], SEQ, SEQ);
  map_2d(enc, &P.maps[M_O_LD], p_o, SEQ, HD);
  map_2d(enc, &P.maps[M_H_LD], p_h, SEQ, FH);
  map_2d(enc, &P.maps[M_X], d_in[0], SEQ, DM);
  map_2d(enc, &P.maps[M_SY_LD], p_sy, SEQ, DM);
  map_2d(enc, &P.maps[M_K], d_in[1], 4 * SK, 128);
  map_2d(enc, &P.maps[M_V], d_in[2], 4 * SK, 128);
  map_3d(enc, &P.maps[M_WIN], d_in[6], DM, FF);
  map_3d(enc, &P.maps[M_WQ], d_in[3], DM, HD);
  map_3d(enc, &P.maps[M_Z2], p_z2, SEQ, FH);
  map_3d(enc, &P.maps[M_WO], d_in[4], HD, DM);
  map_3d(enc, &P.maps[M_WOUT], d_in[9], FH, DM);
  map_2d(enc, &P.maps[M_Z2_ST], p_z2, SEQ, FH, 64);
  map_2d(enc, &P.maps[M_O_ST], p_o, SEQ, HD, 64);
  map_2d(enc, &P.maps[M_H_ST], p_h, SEQ, FH, 64);
  map_2d(enc, &P.maps[M_SY_ST], p_sy, SEQ, DM, 64);
  map_2d(enc, &P.maps[M_OUT], d_out, SEQ, DM, 64);
  P.x = (const bf16*)d_in[0];
  P.b_sp = (const bf16*)d_in[8];
  build_schedule(P);
  mega_kernel<<<NCLUSTERS * 2, 384, SMEM_BYTES, cudaStreamPerThread>>>(P);
}
```

```cpp
#include <cuda_runtime.h>
#include <cuda_bf16.h>
#include <cuda.h>
#include <stdint.h>

typedef __nv_bfloat16 bf16;

constexpr int SEQ = 2048, DM = 1024, HD = 4096, FF = 3584, FH = 1792, SK = 2048, WIN = 512;
constexpr int NCLUSTERS = 64;
constexpr int MAXT = 10;
#define X_DELAY 0
#define LN_DELAY 2

__device__ bf16 g_xn[SEQ * DM];
__device__ bf16 g_z2[SEQ * FH];
__device__ bf16 g_o[SEQ * HD];
__device__ bf16 g_h[SEQ * FH];
__device__ bf16 g_sy[SEQ * DM];
constexpr int F_XN = 0;
constexpr int F_Z2N = 16;
constexpr int F_ST = 32;
constexpr int F_O = 64;
constexpr int F_H = 576;
constexpr int F_SY = 704;
constexpr int F_EPOCH = 768;
constexpr int F_CS = 912;
constexpr int F_COUNT = 1024;
__device__ __align__(16) unsigned int g_flags[F_COUNT];
__device__ float2 g_xstat[SEQ];
__device__ float4 g_csum[8 * 16 * 64];
__device__ float2 g_stats[7 * SEQ];

enum { M_XN = 0, M_WSP, M_O_LD, M_H_LD, M_X, M_SY_LD, M_K, M_V,
       M_WIN, M_WQ, M_Z2, M_WO, M_WOUT,
       M_Z2_ST, M_O_ST, M_H_ST, M_SY_ST, M_OUT,
       M_COUNT };
enum { T_NONE = 0, T_Z2, T_QA, T_Z1, T_G, T_Y, T_S };

struct Params {
  CUtensorMap maps[M_COUNT];
  const bf16* x;
  bf16* out;
  const bf16* b_sp;
  const bf16* kv[2];
  int one;
  unsigned short tasks[NCLUSTERS][MAXT + 2];
  unsigned char krange[NCLUSTERS][2];
};

constexpr int STAGES = 4;
constexpr int STAGE_BYTES = 49152;
constexpr int SM_STG = STAGES * STAGE_BYTES;
constexpr int SM_BAR = SM_STG + 32768;
constexpr int SM_STAT = SM_BAR + 256;
constexpr int SM_CSUM = SM_STAT + 1024;
constexpr int SMEM_BYTES = SM_CSUM + 1024;

template <int TB>
__device__ __forceinline__ void wgmma_ss_n128(float (&d)[64], uint32_t alo, uint32_t blo, int scale_d) {
  asm volatile("{\n.reg .pred p;\n.reg .b64 da, db;\n.reg .b32 hi;\nmov.b32 hi, 0x40000040;\nmov.b64 da, {%64, hi};\nmov.b64 db, {%65, hi};\n"
    "setp.ne.b32 p, %66, 0;\n"
    "wgmma.mma_async.sync.aligned.m64n128k16.f32.bf16.bf16 {%0, %1, %2, %3, %4, %5, %6, %7, %8, %9, %10, %11, %12, %13, %14, %15, %16, %17, %18, %19, %20, %21, %22, %23, %24, %25, %26, %27, %28, %29, %30, %31, %32, %33, %34, %35, %36, %37, %38, %39, %40, %41, %42, %43, %44, %45, %46, %47, %48, %49, %50, %51, %52, %53, %54, %55, %56, %57, %58, %59, %60, %61, %62, %63}, da, db, p, 1, 1, 0, %67;\n}\n"
    : "+f"(d[0]), "+f"(d[1]), "+f"(d[2]), "+f"(d[3]), "+f"(d[4]), "+f"(d[5]), "+f"(d[6]), "+f"(d[7]), "+f"(d[8]), "+f"(d[9]), "+f"(d[10]), "+f"(d[11]), "+f"(d[12]), "+f"(d[13]), "+f"(d[14]), "+f"(d[15]), "+f"(d[16]), "+f"(d[17]), "+f"(d[18]), "+f"(d[19]), "+f"(d[20]), "+f"(d[21]), "+f"(d[22]), "+f"(d[23]), "+f"(d[24]), "+f"(d[25]), "+f"(d[26]), "+f"(d[27]), "+f"(d[28]), "+f"(d[29]), "+f"(d[30]), "+f"(d[31]), "+f"(d[32]), "+f"(d[33]), "+f"(d[34]), "+f"(d[35]), "+f"(d[36]), "+f"(d[37]), "+f"(d[38]), "+f"(d[39]), "+f"(d[40]), "+f"(d[41]), "+f"(d[42]), "+f"(d[43]), "+f"(d[44]), "+f"(d[45]), "+f"(d[46]), "+f"(d[47]), "+f"(d[48]), "+f"(d[49]), "+f"(d[50]), "+f"(d[51]), "+f"(d[52]), "+f"(d[53]), "+f"(d[54]), "+f"(d[55]), "+f"(d[56]), "+f"(d[57]), "+f"(d[58]), "+f"(d[59]), "+f"(d[60]), "+f"(d[61]), "+f"(d[62]), "+f"(d[63])
    : "r"(alo), "r"(blo), "r"(scale_d), "n"(TB));
}

__device__ __forceinline__ uint32_t smem_u32(const void* p) { return (uint32_t)__cvta_generic_to_shared(p); }
__device__ __forceinline__ void mbar_init(uint32_t bar, uint32_t cnt) { asm volatile("mbarrier.init.shared::cta.b64 [%0], %1;" ::"r"(bar), "r"(cnt) : "memory"); }
__device__ __forceinline__ void mbar_expect_tx(uint32_t bar, uint32_t bytes) { asm volatile("mbarrier.arrive.expect_tx.shared::cta.b64 _, [%0], %1;" ::"r"(bar), "r"(bytes) : "memory"); }
__device__ __forceinline__ void mbar_arrive(uint32_t bar) { asm volatile("mbarrier.arrive.shared::cta.b64 _, [%0];" ::"r"(bar) : "memory"); }
__device__ __forceinline__ void mbar_wait(uint32_t bar, uint32_t parity) {
  asm volatile(
      "{\n.reg .pred p;\n.reg .u32 n;\nmov.u32 n, 0;\n"
      "LAB_WAIT:\nmbarrier.try_wait.parity.shared::cta.b64 p, [%0], %1;\n@p bra LAB_DONE;\n"
      "add.u32 n, n, 1;\nsetp.lt.u32 p, n, 4194304;\n@p bra LAB_WAIT;\ntrap;\nLAB_DONE:\n}\n" ::"r"(bar), "r"(parity) : "memory");
}
__device__ __forceinline__ void mbar_wait_idle(uint32_t bar, uint32_t parity) {
  asm volatile(
      "{\n.reg .pred p;\n.reg .u32 n;\nmov.u32 n, 0;\n"
      "LAB_WAIT:\nmbarrier.try_wait.parity.shared::cta.b64 p, [%0], %1, 1000;\n@p bra LAB_DONE;\n"
      "add.u32 n, n, 1;\nsetp.lt.u32 p, n, 4194304;\n@p bra LAB_WAIT;\ntrap;\nLAB_DONE:\n}\n" ::"r"(bar), "r"(parity) : "memory");
}
__device__ __forceinline__ void tma_load_2d(uint32_t dst, const CUtensorMap* tm, uint32_t bar, int c0, int c1) {
  asm volatile("cp.async.bulk.tensor.2d.shared::cluster.global.mbarrier::complete_tx::bytes [%0], [%1, {%3, %4}], [%2];" ::"r"(dst), "l"(tm), "r"(bar), "r"(c0), "r"(c1) : "memory");
}
__device__ __forceinline__ void tma_load_2d_mc(uint32_t dst, const CUtensorMap* tm, uint32_t bar, int c0, int c1) {
  asm volatile("cp.async.bulk.tensor.2d.shared::cluster.global.mbarrier::complete_tx::bytes.multicast::cluster [%0], [%1, {%3, %4}], [%2], %5;" ::"r"(dst), "l"(tm), "r"(bar), "r"(c0), "r"(c1), "h"((uint16_t)3) : "memory");
}
__device__ __forceinline__ void tma_load_3d_mc(uint32_t dst, const CUtensorMap* tm, uint32_t bar, int row, int chunk) {
  asm volatile("cp.async.bulk.tensor.3d.shared::cluster.global.mbarrier::complete_tx::bytes.multicast::cluster [%0], [%1, {%3, %4, %5}], [%2], %6;" ::"r"(dst), "l"(tm), "r"(bar), "r"(0), "r"(row), "r"(chunk), "h"((uint16_t)3) : "memory");
}
__device__ __forceinline__ void tma_load_3d(uint32_t dst, const CUtensorMap* tm, uint32_t bar, int row, int chunk) {
  asm volatile("cp.async.bulk.tensor.3d.shared::cluster.global.mbarrier::complete_tx::bytes [%0], [%1, {%3, %4, %5}], [%2];" ::"r"(dst), "l"(tm), "r"(bar), "r"(0), "r"(row), "r"(chunk) : "memory");
}
__device__ __forceinline__ void tma_store_2d(const CUtensorMap* tm, uint32_t src, int col, int row) {
  asm volatile("cp.async.bulk.tensor.2d.global.shared::cta.bulk_group [%0, {%2, %3}], [%1];" ::"l"(tm), "r"(src), "r"(col), "r"(row) : "memory");
}
__device__ __forceinline__ void wgmma_fence() { asm volatile("wgmma.fence.sync.aligned;" ::: "memory"); }
__device__ __forceinline__ void wgmma_commit() { asm volatile("wgmma.commit_group.sync.aligned;" ::: "memory"); }
template <int N> __device__ __forceinline__ void wgmma_wait() { asm volatile("wgmma.wait_group.sync.aligned %0;" ::"n"(N) : "memory"); }
__device__ __forceinline__ void fence_async() { asm volatile("fence.proxy.async.global;" ::: "memory"); }
__device__ __forceinline__ void fence_async_smem() { asm volatile("fence.proxy.async.shared::cta;" ::: "memory"); }
__device__ __forceinline__ void cluster_arrive() { asm volatile("barrier.cluster.arrive.release;" ::: "memory"); }
__device__ __forceinline__ void cluster_arrive_relaxed() { asm volatile("barrier.cluster.arrive.relaxed;" ::: "memory"); }
__device__ __forceinline__ void cluster_wait() { asm volatile("barrier.cluster.wait.acquire;" ::: "memory"); }
__device__ __forceinline__ void bar_sync(int id, int n) { asm volatile("bar.sync %0, %1;" ::"r"(id), "r"(n) : "memory"); }
__device__ __forceinline__ void bar_arrive(int id, int n) { asm volatile("bar.arrive %0, %1;" ::"r"(id), "r"(n) : "memory"); }
__device__ __forceinline__ uint32_t ld_relaxed(const unsigned int* p) {
  uint32_t v; asm volatile("ld.relaxed.gpu.global.u32 %0, [%1];" : "=r"(v) : "l"(p) : "memory"); return v;
}
__device__ __forceinline__ void fence_acquire() { asm volatile("fence.acquire.gpu;" ::: "memory"); }
__device__ __forceinline__ void red_release(unsigned int* p) { asm volatile("red.release.gpu.global.add.u32 [%0], 1;" ::"l"(p) : "memory"); }
__device__ __forceinline__ uint32_t launch_epoch() { return ld_relaxed(&g_flags[F_EPOCH + blockIdx.x]) + 1; }
__device__ __forceinline__ void flag_wait(int idx, uint32_t target) {
  uint32_t n = 0;
  target *= launch_epoch();
  while ((int)(ld_relaxed(&g_flags[idx]) - target) < 0) {
    __nanosleep(20);
    if (++n > (1u << 22)) __trap();
  }
  fence_acquire();
}
__device__ __forceinline__ uint32_t pack_bf16(float lo, float hi) {
  uint32_t r; asm("cvt.rn.bf16x2.f32 %0, %1, %2;" : "=r"(r) : "f"(hi), "f"(lo)); return r;
}
__device__ __forceinline__ float bf_lo(uint32_t v) { return __uint_as_float(v << 16); }
__device__ __forceinline__ float bf_hi(uint32_t v) { return __uint_as_float(v & 0xffff0000u); }
__device__ __forceinline__ float ex2(float x) { float r; asm("ex2.approx.ftz.f32 %0, %1;" : "=f"(r) : "f"(x)); return r; }
__device__ __forceinline__ float tanh_fast(float x) { float r; asm("tanh.approx.f32 %0, %1;" : "=f"(r) : "f"(x)); return r; }
__device__ __forceinline__ float gelu2_tanh(float x) {
  float u = x * fmaf(x * x, 0.0356774081f, 0.7978845608f);
  return fmaf(x, tanh_fast(u), x);
}
__device__ __forceinline__ uint32_t add_bf2(uint32_t a, uint32_t b) { uint32_t r; asm("add.rn.bf16x2 %0, %1, %2;" : "=r"(r) : "r"(a), "r"(b)); return r; }
__device__ __forceinline__ uint32_t mul_bf2(uint32_t a, uint32_t b) { uint32_t r; asm("mul.rn.bf16x2 %0, %1, %2;" : "=r"(r) : "r"(a), "r"(b)); return r; }
__device__ __forceinline__ uint32_t fma_bf2(uint32_t a, uint32_t b, uint32_t c) { uint32_t r; asm("fma.rn.bf16x2 %0, %1, %2, %3;" : "=r"(r) : "r"(a), "r"(b), "r"(c)); return r; }
__device__ __forceinline__ float silu(float y) {
  float r; asm("rcp.approx.ftz.f32 %0, %1;" : "=f"(r) : "f"(1.0f + ex2(-1.4426950409f * y)));
  return y * r;
}
__device__ __forceinline__ void stmatrix_x4(uint32_t addr, uint32_t r0, uint32_t r1, uint32_t r2, uint32_t r3) {
  asm volatile("stmatrix.sync.aligned.m8n8.x4.shared.b16 [%0], {%1, %2, %3, %4};" ::"r"(addr), "r"(r0), "r"(r1), "r"(r2), "r"(r3) : "memory");
}
__device__ __forceinline__ void ldmatrix_x4(uint32_t addr, uint32_t& r0, uint32_t& r1, uint32_t& r2, uint32_t& r3) {
  asm volatile("ldmatrix.sync.aligned.m8n8.x4.shared.b16 {%0, %1, %2, %3}, [%4];" : "=r"(r0), "=r"(r1), "=r"(r2), "=r"(r3) : "r"(addr) : "memory");
}

#define PROF(slot)
#define PROFT(slot, thr)
#define PROFG(slot)

struct Ctx {
  uint32_t sbase;
  uint32_t d16;
  uint32_t rel;
  uint32_t bars;
  uint32_t it;
  uint32_t sc;
  uint32_t stg;
  uint32_t st_off;
  uint32_t st_sw;
  int wg, t;
  int one;
};
__device__ __forceinline__ uint32_t stage_addr(const Ctx& c, uint32_t it) { return c.sbase + (it & 3) * STAGE_BYTES; }
__device__ __forceinline__ void wait_full(const Ctx& c, uint32_t it) { mbar_wait(c.bars + 8 * (it & 3), (it >> 2) & 1); }
__device__ __forceinline__ void release(const Ctx& c, uint32_t it) {
  if (c.t < 2) asm volatile("mbarrier.arrive.shared::cluster.b64 _, [%0];" ::"r"(c.rel + 8 * (it & 3)) : "memory");
}
__device__ __forceinline__ uint32_t desc_lo(const Ctx& c, uint32_t addr, uint32_t lbo) { return (addr >> 4) - c.d16 + ((lbo >> 4) << 16); }
template <int HALF, bool INIT>
__device__ __forceinline__ void mma_half(const Ctx& c, float (&acc)[64], uint32_t it) {
  const uint32_t st = desc_lo(c, c.sbase, 0) + (it & 3) * (STAGE_BYTES >> 4);
  const uint32_t da = st + c.wg * 512 + (1 << 16), db = st + 1024 + HALF * 1024 + (512 << 16);
#pragma unroll
  for (int kk = 0; kk < 4; kk++) {
    wgmma_ss_n128<1>(acc, da + kk * 2, db + kk * 128, (INIT && kk == 0) ? 0 : 1);
  }
}
__device__ __forceinline__ void stg_acquire(const Ctx& c) { mbar_wait(c.bars + 80 + c.wg * 8, (c.sc & 1) ^ 1); }
__device__ __forceinline__ void stg_commit(Ctx& c) {
  __syncwarp();
  if ((c.t & 31) == 0) mbar_arrive(c.bars + 64 + c.wg * 8);
  c.sc++;
}
template <int OFF>
__device__ __forceinline__ void box_write(const Ctx& c, uint32_t base, const uint32_t (&t)[64]) {
#pragma unroll
  for (int kk = 0; kk < 4; kk++)
    stmatrix_x4(base + c.st_off + (((kk * 2) ^ c.st_sw) << 4), t[OFF + 4 * kk], t[OFF + 4 * kk + 1], t[OFF + 4 * kk + 2], t[OFF + 4 * kk + 3]);
}
__device__ __forceinline__ void acc_write(const Ctx& c, uint32_t base, const float (&s)[64]) {
#pragma unroll
  for (int kk = 0; kk < 8; kk++)
    stmatrix_x4(base + (kk >> 2) * 8192 + c.st_off + ((((kk & 3) * 2) ^ c.st_sw) << 4), pack_bf16(s[8 * kk], s[8 * kk + 1]),
                pack_bf16(s[8 * kk + 2], s[8 * kk + 3]), pack_bf16(s[8 * kk + 4], s[8 * kk + 5]), pack_bf16(s[8 * kk + 6], s[8 * kk + 7]));
}
__device__ __forceinline__ uint32_t opaque(uint32_t v) { asm volatile("" : "+r"(v)); return v; }
__device__ __forceinline__ void half_store(Ctx& c, uint32_t (&t)[64]) {
  stg_acquire(c);
  const uint32_t stg = opaque(c.stg);
  box_write<0>(c, stg, t);
  box_write<16>(c, stg + 8192, t);
  fence_async_smem();
  stg_commit(c);
#pragma unroll
  for (int i = 0; i < 32; i++) asm volatile("mov.b32 %0, %1;" : "=r"(t[i]) : "r"(t[i + 32]));
}
__device__ __forceinline__ void final_half(const Ctx& c, const float (&acc)[64], uint32_t a, uint32_t pitch, const CUtensorMap* m, int col, int row) {
  uint32_t g[32];
#pragma unroll
  for (int kk = 0; kk < 8; kk++)
    ldmatrix_x4(a + (kk >> 2) * pitch + c.st_off + ((((kk & 3) * 2) ^ c.st_sw) << 4), g[4 * kk], g[4 * kk + 1], g[4 * kk + 2], g[4 * kk + 3]);
#pragma unroll
  for (int i = 0; i < 32; i++) g[i] = pack_bf16(acc[2 * i] * bf_lo(g[i]), acc[2 * i + 1] * bf_hi(g[i]));
#pragma unroll
  for (int kk = 0; kk < 8; kk++)
    stmatrix_x4(a + (kk >> 2) * pitch + c.st_off + ((((kk & 3) * 2) ^ c.st_sw) << 4), g[4 * kk], g[4 * kk + 1], g[4 * kk + 2], g[4 * kk + 3]);
  fence_async_smem();
  bar_sync(3 + c.wg, 128);
  if (c.t == 0) {
    fence_async();
    asm volatile("cp.reduce.async.bulk.tensor.2d.global.shared::cta.add.bulk_group [%0, {%2, %3}], [%1];" ::"l"(m), "r"(a), "r"(col), "r"(row) : "memory");
    asm volatile("cp.reduce.async.bulk.tensor.2d.global.shared::cta.add.bulk_group [%0, {%2, %3}], [%1];" ::"l"(m), "r"(a + pitch), "r"(col + 64), "r"(row) : "memory");
    asm volatile("cp.async.bulk.commit_group;" ::: "memory");
  }
}
__device__ __forceinline__ void rotate16(uint32_t (&t)[64]) {
#pragma unroll
  for (int i = 0; i < 16; i++)
    asm volatile("{\n.reg .b32 v;\nmov.b32 v, %0;\nmov.b32 %0, %1;\nmov.b32 %1, %2;\nmov.b32 %2, %3;\nmov.b32 %3, v;\n}\n"
                 : "+r"(t[i]), "+r"(t[i + 16]), "+r"(t[i + 32]), "+r"(t[i + 48]));
}
__device__ __forceinline__ float quad_rcp_sum(float l) {
  l += __shfl_xor_sync(0xffffffffu, l, 1);
  l += __shfl_xor_sync(0xffffffffu, l, 2);
  float r; asm("rcp.approx.ftz.f32 %0, %1;" : "=f"(r) : "f"(l));
  return r;
}
template <int OFF>
__device__ __forceinline__ void capture_plain(uint32_t (&d)[64], const float (&s)[64]) {
#pragma unroll
  for (int i = 0; i < 32; i++) d[OFF + i] = pack_bf16(s[2 * i], s[2 * i + 1]);
}
template <int OFF>
__device__ __forceinline__ void capture_scaled(uint32_t (&d)[64], const float (&s)[64], float r0, float r1) {
#pragma unroll
  for (int i = 0; i < 32; i++) { const float r = (i & 1) ? r1 : r0; d[OFF + i] = pack_bf16(s[2 * i] * r, s[2 * i + 1] * r); }
}
template <int OFF>
__device__ __forceinline__ void capture_gate(uint32_t (&d)[64], const float (&s)[64], float b0, float b1) {
#pragma unroll
  for (int i = 0; i < 32; i++) {
    const float b = (i & 1) ? b1 : b0;
    d[OFF + i] = mul_bf2(pack_bf16(fmaf(s[2 * i], 0.5f, b), fmaf(s[2 * i + 1], 0.5f, b)), d[OFF + i]);
  }
}
__device__ __forceinline__ float as_f(float v) { return v; }
__device__ __forceinline__ float as_f(uint32_t v) { return __uint_as_float(v); }
__device__ __forceinline__ uint32_t as_u(float v) { return __float_as_uint(v); }
__device__ __forceinline__ uint32_t as_u(uint32_t v) { return v; }
__device__ __forceinline__ void set_u(float& d, uint32_t v) { d = __uint_as_float(v); }
__device__ __forceinline__ void set_u(uint32_t& d, uint32_t v) { d = v; }
template <int K0, int K1>
__device__ __forceinline__ void issue_qk(const Ctx& c, float (&s)[64], uint32_t qaddr, uint32_t it) {
  const uint32_t da = desc_lo(c, qaddr, 16), db = desc_lo(c, c.sbase, 16) + (it & 3) * (STAGE_BYTES >> 4);
  wgmma_fence();
#pragma unroll
  for (int kk = K0; kk < K1; kk++) wgmma_ss_n128<0>(s, da + (kk >> 2) * 512 + (kk & 3) * 2, db + (kk >> 2) * 1024 + (kk & 3) * 2, kk == 0 ? 0 : 1);
  wgmma_commit();
}
template <int K0, int K1>
__device__ __forceinline__ void issue_pv(const Ctx& c, float (&o)[64], uint32_t paddr, uint32_t it, int first_scale) {
  const uint32_t da = desc_lo(c, paddr, 16), db = desc_lo(c, c.sbase, 16384) + (it & 3) * (STAGE_BYTES >> 4);
  wgmma_fence();
#pragma unroll
  for (int kk = K0; kk < K1; kk++) wgmma_ss_n128<1>(o, da + (kk >> 2) * 512 + (kk & 3) * 2, db + kk * 128, kk == 0 ? first_scale : 1);
  wgmma_commit();
}
constexpr float SM_SCALE = 0.08838834764831845f * 1.4426950408889634f;
template <typename T>
__device__ __forceinline__ void row_max(const T (&s)[64], float& x0, float& x1) {
  float p[4], q[4];
#pragma unroll
  for (int k = 0; k < 4; k++) { p[k] = fmaxf(as_f(s[4 * k]), as_f(s[4 * k + 1])); q[k] = fmaxf(as_f(s[4 * k + 2]), as_f(s[4 * k + 3])); }
#pragma unroll
  for (int j = 4; j < 16; j++) {
    p[j & 3] = fmaxf(p[j & 3], fmaxf(as_f(s[4 * j]), as_f(s[4 * j + 1])));
    q[j & 3] = fmaxf(q[j & 3], fmaxf(as_f(s[4 * j + 2]), as_f(s[4 * j + 3])));
  }
  x0 = fmaxf(x0, fmaxf(fmaxf(p[0], p[1]), fmaxf(p[2], p[3])));
  x1 = fmaxf(x1, fmaxf(fmaxf(q[0], q[1]), fmaxf(q[2], q[3])));
  x0 = fmaxf(x0, __shfl_xor_sync(0xffffffffu, x0, 1));
  x1 = fmaxf(x1, __shfl_xor_sync(0xffffffffu, x1, 1));
  x0 = fmaxf(x0, __shfl_xor_sync(0xffffffffu, x0, 2));
  x1 = fmaxf(x1, __shfl_xor_sync(0xffffffffu, x1, 2));
}
struct Att {
  float n0, n1, l0, l1, r0, r1;
  uint32_t it, pb, qb;
  bool rescale;
};
template <int K0, int K1, int C0, int C1, typename T, typename TN>
__device__ __forceinline__ void prob_part(T (&s)[64], Att& a, const TN (&sn)[64], int (&top)[2], uint32_t (&pk)[32]) {
#pragma unroll
  for (int kk = K0; kk < K1; kk++) {
    float e[8];
#pragma unroll
    for (int i = 0; i < 8; i++) asm volatile("ex2.approx.ftz.f32 %0, %1;" : "=f"(e[i]) : "f"(fmaf(as_f(s[8 * kk + i]), SM_SCALE, (i & 2) ? a.n1 : a.n0)));
    a.l0 += (e[0] + e[1]) + (e[4] + e[5]);
    a.l1 += (e[2] + e[3]) + (e[6] + e[7]);
#pragma unroll
    for (int i = 0; i < 4; i++) asm volatile("cvt.rn.bf16x2.f32 %0, %1, %2;" : "=r"(pk[4 * kk + i]) : "f"(e[2 * i + 1]), "f"(e[2 * i]));
  }
#pragma unroll
  for (int i = 8 * C0; i < 8 * C1; i += 2)
    top[(i >> 1) & 1] = __vimax3_s32(top[(i >> 1) & 1], (int)as_u(sn[i]), (int)as_u(sn[i + 1]));
  asm volatile("" : "+f"(a.l0), "+f"(a.l1), "+r"(top[0]), "+r"(top[1]));
}
#define AS1 2
#define AS2 7
#define ONCE(body) { int rep_ = 0; _Pragma("unroll 1") do { body; } while (++rep_ < c.one); }
template <int MODE>
__device__ __forceinline__ void att_step(Ctx& c, Att& a, int j, float (&s)[64], float (&sn)[64], float (&o)[64]) {
  int top[2] = {0, 0};
  uint32_t pk[32];
  const uint32_t itk = a.it + 1, itv = a.it + (MODE == 1 ? 2 : 1);
  a.it = itv;
  if (MODE != 0) {
    if (MODE == 1) wait_full(c, itk);
    wait_full(c, itv);
    fence_async_smem();
    if (MODE == 1 && j == 5) stg_commit(c);
    bar_sync(1 + c.wg, 256);
    if (MODE == 1) ONCE((issue_qk<0, 8>(c, sn, j < 3 ? c.stg : a.qb, itk)))
    else ONCE((issue_pv<0, 8>(c, o, a.pb, itv, 1), bar_arrive(2 - c.wg, 256)));
  }
  prob_part<0, AS1, 0, 0>(s, a, sn, top, pk);
  if (MODE == 1) ONCE((issue_pv<0, 8>(c, o, a.pb, itv, (j - 1) & 3), bar_arrive(2 - c.wg, 256)));
  prob_part<AS1, AS2, 0, 0>(s, a, sn, top, pk);
  ONCE(wgmma_wait<0>());
  if (MODE == 1) release(c, itk);
  release(c, itv);
  if (MODE == 0) wait_full(c, itv + 1 + c.wg);
  if (MODE == 1 && j == 6) { stg_acquire(c); a.pb = c.stg; }
#pragma unroll
  for (int kk = 0; kk < AS2; kk++)
    stmatrix_x4(a.pb + (kk >> 2) * 8192 + c.st_off + ((((kk & 3) * 2) ^ c.st_sw) << 4), pk[4 * kk], pk[4 * kk + 1], pk[4 * kk + 2], pk[4 * kk + 3]);
  prob_part<AS2, 8, 0, MODE == 2 ? 0 : 8>(s, a, sn, top, pk);
#pragma unroll
  for (int kk = AS2; kk < 8; kk++)
    stmatrix_x4(a.pb + (kk >> 2) * 8192 + c.st_off + ((((kk & 3) * 2) ^ c.st_sw) << 4), pk[4 * kk], pk[4 * kk + 1], pk[4 * kk + 2], pk[4 * kk + 3]);
  const float t0 = (16.f - a.n0) * (1.f / SM_SCALE), t1 = (16.f - a.n1) * (1.f / SM_SCALE);
  const bool over = MODE != 2 && __any_sync(0xffffffffu, top[0] > __float_as_int(t0) || top[1] > __float_as_int(t1));
  if (MODE != 0 && a.rescale) {
#pragma unroll
    for (int i = 0; i < 16; i++) { o[4 * i] *= a.r0; o[4 * i + 1] *= a.r0; o[4 * i + 2] *= a.r1; o[4 * i + 3] *= a.r1; }
    a.rescale = false;
  }
  if (MODE == 1 && j == 4) acc_write(c, c.stg, o);
  if (MODE != 2 && (j == 3 || over)) {
    float x0 = -INFINITY, x1 = -INFINITY;
    row_max(sn, x0, x1);
    x0 *= -SM_SCALE; x1 *= -SM_SCALE;
    if (j == 3) {
      a.r0 = quad_rcp_sum(a.l0); a.r1 = quad_rcp_sum(a.l1);
      a.l0 = 0.f; a.l1 = 0.f;
    } else {
      x0 = fminf(x0, a.n0); x1 = fminf(x1, a.n1);
      a.r0 = ex2(x0 - a.n0); a.r1 = ex2(x1 - a.n1);
      a.l0 *= a.r0; a.l1 *= a.r1;
    }
    a.n0 = x0; a.n1 = x1;
    a.rescale = true;
  }
}

__device__ __forceinline__ float warp_sum(float v) {
#pragma unroll
  for (int o = 16; o > 0; o >>= 1) v += __shfl_xor_sync(0xffffffffu, v, o);
  return v;
}
__device__ __forceinline__ void ln_stats(uint32_t (&t)[64], float& r0, float& b0, float& r1, float& b1, uint32_t zero) {
  float m0 = 0.f, m1 = 0.f;
#pragma unroll
  for (int i = 0; i < 16; i++) { m0 += bf_lo(t[i]) + bf_hi(t[i]); m1 += bf_lo(t[16 + i]) + bf_hi(t[16 + i]); }
#pragma unroll
  for (int o = 16; o > 0; o >>= 1) { m0 += __shfl_xor_sync(0xffffffffu, m0, o); m1 += __shfl_xor_sync(0xffffffffu, m1, o); }
  m0 *= 1.0f / DM; m1 *= 1.0f / DM;
#pragma unroll
  for (int i = 0; i < 32; i++) asm volatile("xor.b32 %0, %0, %1;" : "+r"(t[i]) : "r"(zero));
  float q0 = 0.f, q1 = 0.f;
#pragma unroll
  for (int i = 0; i < 16; i++) {
    const float a = bf_lo(t[i]) - m0, b = bf_hi(t[i]) - m0, c = bf_lo(t[16 + i]) - m1, d = bf_hi(t[16 + i]) - m1;
    q0 = fmaf(a, a, fmaf(b, b, q0)); q1 = fmaf(c, c, fmaf(d, d, q1));
  }
#pragma unroll
  for (int o = 16; o > 0; o >>= 1) { q0 += __shfl_xor_sync(0xffffffffu, q0, o); q1 += __shfl_xor_sync(0xffffffffu, q1, o); }
  r0 = rsqrtf(q0 * (1.0f / DM) + 1e-5f); b0 = -m0 * r0;
  r1 = rsqrtf(q1 * (1.0f / DM) + 1e-5f); b1 = -m1 * r1;
}
__device__ __forceinline__ uint32_t ln_apply(uint32_t w, float r, float b) { return pack_bf16(fmaf(bf_lo(w), r, b), fmaf(bf_hi(w), r, b)); }
template <int OFF>
__device__ __forceinline__ void capture_fixup(uint32_t (&d)[64], const float (&acc)[64], uint32_t csum, float r0, float b0, float r1, float b1) {
#pragma unroll
  for (int j = 0; j < 16; j++) {
    float c0, c1;
    asm volatile("ld.shared.v2.f32 {%0, %1}, [%2];" : "=f"(c0), "=f"(c1) : "r"(csum + j * 32) : "memory");
    d[OFF + 2 * j] = pack_bf16(fmaf(acc[4 * j], r0, b0 * c0), fmaf(acc[4 * j + 1], r0, b0 * c1));
    d[OFF + 2 * j + 1] = pack_bf16(fmaf(acc[4 * j + 2], r1, b1 * c0), fmaf(acc[4 * j + 3], r1, b1 * c1));
  }
}
__device__ __forceinline__ void ln_fixup(float (&acc)[64], uint32_t csum, float r0, float b0, float r1, float b1) {
#pragma unroll
  for (int j = 0; j < 16; j++) {
    float c0, c1;
    asm volatile("ld.shared.v2.f32 {%0, %1}, [%2];" : "=f"(c0), "=f"(c1) : "r"(csum + j * 32) : "memory");
    acc[4 * j] = fmaf(acc[4 * j], r0, b0 * c0); acc[4 * j + 1] = fmaf(acc[4 * j + 1], r0, b0 * c1);
    acc[4 * j + 2] = fmaf(acc[4 * j + 2], r1, b1 * c0); acc[4 * j + 3] = fmaf(acc[4 * j + 3], r1, b1 * c1);
  }
}

struct Prod {
  uint32_t sbase, bars, it, rank, lane;
};
__device__ __forceinline__ uint32_t prod_acquire(Prod& p, uint32_t bytes) {
  uint32_t s = p.it & 3;
  mbar_wait(p.bars + 32 + 8 * s, ((p.it >> 2) & 1) ^ 1);
  if (p.lane == 0) mbar_expect_tx(p.bars + 8 * s, bytes);
  p.it++;
  return s;
}
__device__ __forceinline__ void dep_wait(const Prod& p, uint32_t& ready, int base, int n, uint32_t target, int i) {
  if ((ready >> i) & 1) return;
  target *= launch_epoch();
  uint32_t spins = 0;
  do {
    const bool ok = (int)p.lane < n && (int)(ld_relaxed(&g_flags[base + p.lane]) - target) >= 0;
    ready = __ballot_sync(0xffffffffu, ok);
    if (++spins > (1u << 22)) __trap();
  } while (!((ready >> i) & 1));
  fence_acquire();
  __syncwarp();
  fence_async();
}
__device__ __forceinline__ void prod_gemm(Prod& p, const CUtensorMap* mA, int arow, const CUtensorMap* mB, int chunk, int k0, int k1,
                                          int base, int n, uint32_t target, int shift, uint32_t& ready) {
#pragma unroll 1
  for (int k = k0; k < k1; k++) {
    dep_wait(p, ready, base, n, target, k >> shift);
    uint32_t s = prod_acquire(p, STAGE_BYTES);
    uint32_t a = p.sbase + s * STAGE_BYTES;
    if (p.lane == 0) {
      tma_load_3d_mc(a + 16384 + p.rank * 16384, mB, p.bars + 8 * s, k * 64, chunk + p.rank * 2);
      tma_load_2d(a, mA, p.bars + 8 * s, k * 64, arow);
    }
  }
}

__global__ void __cluster_dims__(2, 1, 1) __launch_bounds__(384, 1) mega_kernel(const __grid_constant__ Params P) {
  extern __shared__ __align__(1024) uint8_t smem_raw[];
  const uint32_t sbase = smem_u32(smem_raw);
  const uint32_t bars = sbase + SM_BAR;
  const int tid = threadIdx.x, lane = tid & 31;
  const int warp = __shfl_sync(0xffffffffu, tid >> 5, 0), wg = warp >> 2;
  const uint32_t rank = blockIdx.x & 1;
  const int cid = blockIdx.x >> 1;
  PROFG(60); PROF(61);

  if (tid == 256) {
    for (int s = 0; s < STAGES; s++) { mbar_init(bars + 8 * s, 1); mbar_init(bars + 32 + 8 * s, 4); }
    for (int w = 0; w < 2; w++) { mbar_init(bars + 64 + 8 * w, 4); mbar_init(bars + 80 + 8 * w, 1); mbar_init(bars + 112 + 8 * w, 4); }
    for (int w = 0; w < 2; w++) { mbar_init(bars + 128 + 8 * w, 4); mbar_init(bars + 144 + 8 * w, 1); }
    mbar_init(bars + 160, 10);
    mbar_init(bars + 168, 3);
    mbar_init(bars + 176, 1);
    mbar_init(bars + 184, 1);
    asm volatile("fence.mbarrier_init.release.cluster;" ::: "memory");
  }

  __syncwarp();
  cluster_arrive_relaxed();

  if (wg == 2) {
    if (warp == 9 && lane < M_COUNT) asm volatile("prefetch.tensormap [%0];" ::"l"(&P.maps[lane]) : "memory");
    asm volatile("setmaxnreg.dec.sync.aligned.u32 40;");
    cluster_wait();
    if (warp == 8) {
      Prod p{sbase, bars, 0, rank, (uint32_t)lane};
      PROFT(43, 256);
#pragma unroll 1
      for (int ti = 0; ti < MAXT; ti++) {
        const uint32_t task = P.tasks[cid][ti];
        const int type = task & 7, mb = ((task >> 4) & 15) * 2 + rank, idx = task >> 8;
        if (type == T_NONE) break;
        const int arow = mb * 128;
        int mA = M_XN, mB = M_WIN, chunk = idx * 4, nk = 16, base = F_XN + mb, n = 1, shift = 5;
        uint32_t target = 8;
        int k0 = 0;
        if (type == T_Z2) chunk += FH / 64;
        else if (type == T_QA) mB = M_WQ;
        else if (type == T_G) { mA = M_WSP; mB = M_Z2; nk = 32; base = F_Z2N; n = 16; target = 14; shift = 1; }
        else if (type == T_S) { mA = M_O_LD; mB = M_WO; k0 = P.krange[cid][0]; nk = P.krange[cid][1]; base = F_O + mb * 32; n = 32; target = 2; shift = 1; }
        else if (type == T_Y) { mA = M_H_LD; mB = M_WOUT; nk = 28; base = F_H + mb * 8; n = 7; target = 2; shift = 2; }
        if (ti == 0) { mA = M_X; n = 0; }
        uint32_t ready = n ? 0 : 0xffffffffu;
        prod_gemm(p, &P.maps[mA], arow, &P.maps[mB], chunk, k0, nk, base, n, target, shift, ready);
        if (type == T_QA) {
          const int kvrow = (idx >> 2) * SK + (SK - WIN);
#pragma unroll 1
          for (int j = 0; j < 16; j++) {
            const bool isK = j < 2 || (j < 14 && !(j & 1));
            const int ch = (j < 2 ? j : j >= 14 ? j - 12 : isK ? (j >> 1) + 1 : (j >> 1) - 1) & 3;
            uint32_t s = prod_acquire(p, 32768);
            if (lane == 0) tma_load_2d_mc(sbase + s * STAGE_BYTES + rank * 16384, &P.maps[isK ? M_K : M_V], bars + 8 * s, rank * 64, kvrow + ch * 128);
          }
        }
        if (type == T_S) {
          ready = 0;
          dep_wait(p, ready, F_SY + mb * 4 + idx, 1, 2, 0);
          const uint32_t s = prod_acquire(p, 32768);
          if (lane < 2) tma_load_2d(sbase + s * STAGE_BYTES + lane * 16384, &P.maps[M_SY_LD], bars + 8 * s, idx * 256 + 128 + lane * 64, arow);
        }
      }
    } else if (warp == 9 || warp == 10) {
      const int w = warp - 9;
      {
        const uint32_t task = P.tasks[cid][0];
        const int type = task & 7, mb = ((task >> 4) & 15) * 2 + rank, tile = cid & 7;
        const uint32_t slab = sbase + SM_STG + w * 16384;
        for (int i = 0; i <= X_DELAY; i++) mbar_wait(bars + 8 * (i & 3), (i >> 2) & 1);
        if (lane == 0) {
          const size_t off = (size_t)(blockIdx.x * 16 + w * 8) * DM;
          mbar_expect_tx(bars + 176 + 8 * w, 16384);
          asm volatile("cp.async.bulk.shared::cluster.global.mbarrier::complete_tx::bytes [%0], [%1], 16384, [%2];" ::"r"(slab), "l"(P.x + off), "r"(bars + 176 + 8 * w) : "memory");
          mbar_wait(bars + 176 + 8 * w, 0);
          asm volatile("cp.async.bulk.global.shared::cta.bulk_group [%0], [%1], 16384;" ::"l"(P.out + off), "r"(slab) : "memory");
          asm volatile("cp.async.bulk.commit_group;" ::: "memory");
          asm volatile("cp.async.bulk.wait_group.read 0;" ::: "memory");
          mbar_wait(bars + 112 + 8 * w, 0);
          fence_async_smem();
          mbar_expect_tx(bars + 176 + 8 * w, 16384);
          tma_load_3d(slab, &P.maps[type == T_QA ? M_WQ : M_WIN], bars + 176 + 8 * w, mb * 64, (type == T_Z2 ? FH / 64 : 0) + (task >> 8) * 4 + w * 2);
        }
        __syncwarp();
        mbar_wait(bars + 176 + 8 * w, 1);
        float4 a = make_float4(0.f, 0.f, 0.f, 0.f);
#pragma unroll 1
        for (int r = 0; r < 64; r += 8) {
          uint32_t v0[8], v1[8];
#pragma unroll
          for (int i = 0; i < 8; i++)
            asm volatile("ld.shared.v2.b32 {%0, %1}, [%2];" : "=r"(v0[i]), "=r"(v1[i]) : "r"(slab + (lane >> 4) * 8192 + (r + i) * 128 + ((((lane & 15) >> 1) ^ i) << 4) + (lane & 1) * 8) : "memory");
#pragma unroll
          for (int i = 0; i < 8; i += 4) {
            const uint32_t p0 = add_bf2(add_bf2(v0[i], v0[i + 1]), add_bf2(v0[i + 2], v0[i + 3]));
            const uint32_t p1 = add_bf2(add_bf2(v1[i], v1[i + 1]), add_bf2(v1[i + 2], v1[i + 3]));
            a.x += bf_lo(p0); a.y += bf_hi(p0); a.z += bf_lo(p1); a.w += bf_hi(p1);
          }
        }
        g_csum[(tile * 16 + mb) * 64 + w * 32 + lane] = a;
        __syncwarp();
        if (lane == 0) {
          asm volatile("cp.async.bulk.wait_group 0;" ::: "memory");
          mbar_arrive(bars + 160);
          red_release(&g_flags[F_CS + tile * 2 + w]);
        }
        __syncwarp();
        flag_wait(F_CS + tile * 2 + w, 16);
        a = make_float4(0.f, 0.f, 0.f, 0.f);
#pragma unroll
        for (int r = 0; r < 16; r++) {
          const float4 v = __ldcg(&g_csum[(tile * 16 + r) * 64 + w * 32 + lane]);
          a.x += v.x; a.y += v.y; a.z += v.z; a.w += v.w;
        }
        asm volatile("st.shared.v4.f32 [%0], {%1, %2, %3, %4};" ::"r"(sbase + SM_CSUM + w * 512 + lane * 16), "f"(a.x), "f"(a.y), "f"(a.z), "f"(a.w) : "memory");
        __syncwarp();
        if (lane == 0) mbar_arrive(bars + 168);
        PROFT(50, 288);
      }
      if (lane == 0) {
        uint32_t sc = 0;
#pragma unroll 1
        for (int ti = 0; ti < MAXT; ti++) {
          const uint32_t task = P.tasks[cid][ti];
          const int type = task & 7, mb = ((task >> 4) & 15) * 2 + rank, idx = task >> 8;
          if (type == T_NONE) break;
          if (type == T_S) {
            flag_wait(F_SY + mb * 4 + idx, 2);
            fence_async();
            mbar_expect_tx(bars + 176 + 8 * w, 16384);
            tma_load_2d(sbase + SM_STG + w * 16384, &P.maps[M_SY_ST], bars + 176 + 8 * w, idx * 256, mb * 128 + w * 64);
            tma_load_2d(sbase + SM_STG + w * 16384 + 8192, &P.maps[M_SY_ST], bars + 176 + 8 * w, idx * 256 + 64, mb * 128 + w * 64);
          }
          if (type == T_Z1 || type == T_S) continue;
          const int mi = type == T_Z2 ? M_Z2_ST : type == T_QA ? M_O_ST : type == T_G ? M_H_ST : M_SY_ST;
          const int f = type == T_Z2 ? F_Z2N + mb : type == T_QA ? F_O + mb * 32 + idx * 2 : type == T_G ? F_H + mb * 8 + idx : F_SY + mb * 4 + idx;
#pragma unroll 1
          for (int q = 0; q < 2; q++, sc++) {
            mbar_wait_idle(bars + 64 + w * 8, sc & 1);
            tma_store_2d(&P.maps[mi], sbase + SM_STG + w * 16384, idx * 256 + q * 128, mb * 128 + w * 64);
            tma_store_2d(&P.maps[mi], sbase + SM_STG + w * 16384 + 8192, idx * 256 + q * 128 + 64, mb * 128 + w * 64);
            asm volatile("cp.async.bulk.commit_group;" ::: "memory");
            asm volatile("cp.async.bulk.wait_group.read 0;" ::: "memory");
            mbar_arrive(bars + 80 + w * 8);
            if (q == 1 || type == T_QA) {
              asm volatile("cp.async.bulk.wait_group 0;" ::: "memory");
              red_release(&g_flags[f + (type == T_QA ? q : 0)]);
            }
          }
        }
      }
    } else {
      const uint32_t task = P.tasks[cid][0];
      {
        const int mb = ((task >> 4) & 15) * 2 + rank;
        if (blockIdx.x < 128) {
          mbar_wait(bars + 24, 0);
          const size_t off = ((size_t)(blockIdx.x >> 5) * SK + (SK - WIN) + (blockIdx.x & 31) * 16) * 128 + lane * 64;
          asm volatile("prefetch.global.L2 [%0];" ::"l"(P.kv[0] + off));
          asm volatile("prefetch.global.L2 [%0];" ::"l"(P.kv[1] + off));
        }
        mbar_wait(bars + 160, 0);
        if (lane == 0) red_release(&g_flags[F_XN + (blockIdx.x >> 3)]);
        __syncwarp();
        flag_wait(F_XN + mb, 8);
        const float4 u0 = __ldcg(reinterpret_cast<const float4*>(&g_xstat[mb * 128]) + lane);
        const float4 u1 = __ldcg(reinterpret_cast<const float4*>(&g_xstat[mb * 128 + 64]) + lane);
        asm volatile("st.shared.v4.f32 [%0], {%1, %2, %3, %4};" ::"r"(sbase + SM_STAT + lane * 16), "f"(u0.x), "f"(u0.y), "f"(u0.z), "f"(u0.w) : "memory");
        asm volatile("st.shared.v4.f32 [%0], {%1, %2, %3, %4};" ::"r"(sbase + SM_STAT + 512 + lane * 16), "f"(u1.x), "f"(u1.y), "f"(u1.z), "f"(u1.w) : "memory");
        __syncwarp();
        if (lane == 0) mbar_arrive(bars + 168);
        PROFT(42, 352);
      }
      if ((task & 7) == T_Z2) {
        const int mb = ((task >> 4) & 15) * 2 + rank, idx = task >> 8;
        const uint32_t st = sbase + SM_STAT + lane * 16;
#pragma unroll 1
        for (int w = 0; w < 2; w++) {
          float4 v;
          mbar_wait(bars + 128 + 8 * w, 0);
          asm volatile("ld.shared.v4.f32 {%0, %1, %2, %3}, [%4];" : "=f"(v.x), "=f"(v.y), "=f"(v.z), "=f"(v.w) : "r"(st + w * 512) : "memory");
          *reinterpret_cast<float4*>(&g_stats[idx * SEQ + mb * 128 + w * 64 + lane * 2]) = v;
          __syncwarp();
          if (lane == 0) red_release(&g_flags[F_ST + mb * 2 + w]);
        }
#pragma unroll 1
        for (int w = 0; w < 2; w++) {
          flag_wait(F_ST + mb * 2 + w, 7);
          float4 a = make_float4(0.f, 0.f, 0.f, 0.f);
#pragma unroll
          for (int i = 0; i < 7; i++) {
            const float4 v = __ldcg(reinterpret_cast<const float4*>(&g_stats[i * SEQ + mb * 128 + w * 64 + lane * 2]));
            a.x += v.x; a.y += v.y; a.z += v.z; a.w += v.w;
          }
          const float m0 = a.x * (1.0f / FH), m1 = a.z * (1.0f / FH);
          const float q0 = rsqrtf(fmaxf(fmaf(-m0, m0, a.y * (1.0f / FH)), 0.f) + 4e-5f);
          const float q1 = rsqrtf(fmaxf(fmaf(-m1, m1, a.w * (1.0f / FH)), 0.f) + 4e-5f);
          asm volatile("st.shared.v4.b32 [%0], {%1, %2, %3, %4};" ::"r"(st + w * 512), "r"(pack_bf16(q0, q0)), "r"(pack_bf16(-m0 * q0, -m0 * q0)),
                       "r"(pack_bf16(q1, q1)), "r"(pack_bf16(-m1 * q1, -m1 * q1)) : "memory");
          __syncwarp();
          if (lane == 0) mbar_arrive(bars + 144 + 8 * w);
        }
      }
    }
  } else {
    asm volatile("setmaxnreg.inc.sync.aligned.u32 232;");
    uint32_t t[64];
#pragma unroll
    for (int i = 0; i < 64; i++) t[i] = 0;
    cluster_wait();
    PROF(62);

    Ctx c;
    c.sbase = sbase; c.bars = bars; c.it = 0; c.sc = 0; c.wg = wg; c.t = tid & 127; c.one = P.one;
    c.d16 = (sbase & ~0x3FFFFu) >> 4;
    asm volatile("mapa.shared::cluster.u32 %0, %1, %2;" : "=r"(c.rel) : "r"(bars + 32), "r"(tid & 1));
    c.stg = sbase + SM_STG + wg * 16384;
    {
      const int row = (warp & 3) * 16 + ((lane >> 3) & 1) * 8 + (lane & 7);
      c.st_off = row * 128;
      c.st_sw = (lane >> 4) ^ (lane & 7);
    }
    if (wg == 1) bar_arrive(1, 256);
    float accA[64], accB[64];
    int pend = 2, ptype = T_NONE;
    float s0 = 0.f, s1 = 0.f, q0 = 0.f, q1 = 0.f;
    wait_full(c, 0);
    PROF(40);
    wgmma_fence();
    mma_half<0, true>(c, accA, 0);
    mma_half<1, true>(c, accB, 0);
    wgmma_commit();
#pragma unroll 1
    for (int ti = 0;; ti++) {
      const uint32_t task = P.tasks[cid][ti];
      const int type = task & 7, mb = ((task >> 4) & 15) * 2 + rank;
      const bool next = P.tasks[cid][ti + 1] != 0;
      const bool is_qa = type == T_QA;
      PROF(ti * 4);
      uint32_t it = c.it + 1;
      const uint32_t nk = type == T_G ? 32 : type == T_Y ? 28 : (type == T_S) ? P.krange[cid][1] - P.krange[cid][0] : 16;
      const uint32_t last = c.it + nk - 1;
      const uint32_t period = type == T_G ? 4 : (ptype == T_Y && nk >= 22) ? 3 : 2;
      uint32_t slot = it + (wg ? period >> 1 : 0) + (ti == 0 ? LN_DELAY : 0);
#pragma unroll 1
      for (; it < last; it++) {
        wait_full(c, it);
        wgmma_fence();
        mma_half<0, false>(c, accA, it);
        mma_half<1, false>(c, accB, it);
        wgmma_commit();
        wgmma_wait<1>();
        release(c, it - 1);
        if (it == slot) {
          const uint32_t stat = sbase + SM_STAT + (wg * 64 + (warp & 3) * 16 + (lane >> 2)) * 8;
          slot += period;
          if (pend > 2) {
            if (ptype == T_Z1) {
#pragma unroll
              for (int i = 0; i < 16; i++) t[i] = pack_bf16(gelu2_tanh(bf_lo(t[i])), gelu2_tanh(bf_hi(t[i])));
            } else if (ptype == T_Y) {
#pragma unroll
              for (int i = 0; i < 16; i++) t[i] = pack_bf16(silu(bf_lo(t[i])), silu(bf_hi(t[i])));
            } else {
#pragma unroll
              for (int i = 0; i < 16; i++) {
                const float a = gelu2_tanh(bf_lo(t[i])), b = gelu2_tanh(bf_hi(t[i]));
                t[i] = pack_bf16(a, b);
                if (i & 1) { s1 += a + b; q1 = fmaf(a, a, fmaf(b, b, q1)); }
                else { s0 += a + b; q0 = fmaf(a, a, fmaf(b, b, q0)); }
              }
            }
            rotate16(t);
            if (pend == 3) {
              if (ptype == T_Z1) pend = 1;
              else if (ptype == T_Z2) {
                slot += period;
#pragma unroll
                for (int o = 1; o < 4; o <<= 1) {
                  s0 += __shfl_xor_sync(0xffffffffu, s0, o); q0 += __shfl_xor_sync(0xffffffffu, q0, o);
                  s1 += __shfl_xor_sync(0xffffffffu, s1, o); q1 += __shfl_xor_sync(0xffffffffu, q1, o);
                }
                if ((lane & 3) == 0) {
                  asm volatile("st.shared.v2.f32 [%0], {%1, %2};" ::"r"(stat), "f"(s0), "f"(q0) : "memory");
                  asm volatile("st.shared.v2.f32 [%0], {%1, %2};" ::"r"(stat + 64), "f"(s1), "f"(q1) : "memory");
                }
                __syncwarp();
                if (lane == 0) mbar_arrive(bars + 128 + 8 * wg);
              }
            }
          } else if (ptype == T_NONE) {
            if (pend == 2) {
              mbar_wait(bars + 176 + 8 * wg, 0);
#pragma unroll
              for (int i = 0; i < 8; i++)
                asm volatile("ld.shared.v4.u32 {%0, %1, %2, %3}, [%4];" : "=r"(t[4 * i]), "=r"(t[4 * i + 1]), "=r"(t[4 * i + 2]), "=r"(t[4 * i + 3]) : "r"(c.stg + (warp & 3) * 4096 + i * 512 + lane * 16) : "memory");
              __syncwarp();
              if (lane == 0) mbar_arrive(bars + 112 + 8 * wg);
              ln_stats(t, s0, q0, s1, q1, t[32]);
            }
            if (pend == 1) {
              const int row = blockIdx.x * 16 + warp * 2;
              uint4* xo = reinterpret_cast<uint4*>(g_xn + (size_t)row * DM);
#pragma unroll
              for (int i = 0; i < 8; i++) {
                const float r = i < 4 ? s0 : s1, b = i < 4 ? q0 : q1;
                xo[i * 32 + lane] = make_uint4(ln_apply(t[4 * i], r, b), ln_apply(t[4 * i + 1], r, b), ln_apply(t[4 * i + 2], r, b), ln_apply(t[4 * i + 3], r, b));
              }
              if (lane == 0) *reinterpret_cast<float4*>(&g_xstat[row]) = make_float4(s0, q0, s1, q1);
              __syncwarp();
              if (lane == 0) mbar_arrive(bars + 160);
              PROF(41);
            }
          } else {
            if (ptype == T_Z2) {
              uint32_t a0, b0, a1, b1;
              mbar_wait(bars + 144 + 8 * wg, 0);
              asm volatile("ld.shared.v2.b32 {%0, %1}, [%2];" : "=r"(a0), "=r"(b0) : "r"(stat) : "memory");
              asm volatile("ld.shared.v2.b32 {%0, %1}, [%2];" : "=r"(a1), "=r"(b1) : "r"(stat + 64) : "memory");
#pragma unroll
              for (int i = 0; i < 32; i++) t[i] = fma_bf2(t[i], (i & 1) ? a1 : a0, (i & 1) ? b1 : b0);
            }
            half_store(c, t);
          }
          if (--pend == 0) slot = last;
        }
      }
      uint32_t b0 = 0, b1 = 0;
      if (type == T_G) {
        const bf16* bp = P.b_sp + mb * 128 + wg * 64 + (warp & 3) * 16 + (lane >> 2);
        asm volatile("ld.global.nc.u16 %0, [%1];" : "=r"(b0) : "l"(bp));
        asm volatile("ld.global.nc.u16 %0, [%1];" : "=r"(b1) : "l"(bp + 8));
      }
      wait_full(c, it);
      if (is_qa) {
        stg_acquire(c);
        bar_sync(1 + wg, 256);
      }
      wgmma_fence();
      mma_half<0, false>(c, accA, it);
      wgmma_commit();
      mma_half<1, false>(c, accB, it);
      wgmma_commit();
      if (is_qa) bar_arrive(2 - wg, 256);
      wgmma_wait<1>();
      release(c, it - 1);
      it++;
      PROF(ti * 4 + 1);
      if (type == T_S) {
        const int col = (task >> 8) * 256, row = mb * 128 + wg * 64;
        PROF(44);
        mbar_wait(bars + 176 + 8 * wg, 0);
        PROF(45);
        final_half(c, accA, c.stg, 8192, &P.maps[M_OUT], col, row);
        PROF(46);
        wgmma_wait<0>();
        wait_full(c, it);
        PROF(47);
        final_half(c, accB, stage_addr(c, it) + wg * 8192, 16384, &P.maps[M_OUT], col + 128, row);
        PROF(48);
        if (c.t == 0) asm volatile("cp.async.bulk.wait_group.read 0;" ::: "memory");
        PROF(ti * 4 + 2);
        break;
      }
      if (ti == 0) {
        const uint32_t stat = sbase + SM_STAT + (wg * 64 + (warp & 3) * 16 + (lane >> 2)) * 8;
        mbar_wait(bars + 168, 0);
        asm volatile("ld.shared.v2.f32 {%0, %1}, [%2];" : "=f"(s0), "=f"(q0) : "r"(stat) : "memory");
        asm volatile("ld.shared.v2.f32 {%0, %1}, [%2];" : "=f"(s1), "=f"(q1) : "r"(stat + 64) : "memory");
        if (is_qa) {
          wgmma_wait<0>();
          ln_fixup(accA, sbase + SM_CSUM + (lane & 3) * 8, s0, q0, s1, q1);
          ln_fixup(accB, sbase + SM_CSUM + 512 + (lane & 3) * 8, s0, q0, s1, q1);
        }
      }
      if (is_qa) {
        acc_write(c, opaque(c.stg), accA);
        Att a;
        a.qb = stage_addr(c, it + wg) + 32768;
        a.pb = stage_addr(c, it + 2 + wg) + 32768;
        float accC[64];
#pragma unroll
        for (int i = 0; i < 64; i++) accC[i] = 0.f;
        wait_full(c, it);
        wait_full(c, it + 1);
        fence_async_smem();
        bar_sync(1 + wg, 256);
        issue_qk<0, 8>(c, accA, c.stg, it);
        wgmma_wait<1>();
        release(c, it - 1);
        acc_write(c, a.qb, accB);
        issue_qk<0, 8>(c, accC, c.stg, it + 1);
        bar_arrive(2 - wg, 256);
        wgmma_wait<1>();
        release(c, it);
        a.it = it; a.l0 = 0.f; a.l1 = 0.f; a.r0 = 0.f; a.r1 = 0.f; a.rescale = false;
        {
          float x0 = -INFINITY, x1 = -INFINITY;
          row_max(accA, x0, x1);
          a.n0 = -x0 * SM_SCALE; a.n1 = -x1 * SM_SCALE;
        }
        att_step<0>(c, a, 0, accA, accC, accB);
#pragma unroll 1
        for (int j = 1; j < 7; j += 2) {
          att_step<1>(c, a, j, accC, accA, accB);
          att_step<1>(c, a, j + 1, accA, accC, accB);
        }
        att_step<2>(c, a, 7, accC, accA, accB);
        it = a.it + 1;
        wait_full(c, it);
        fence_async_smem();
        bar_sync(1 + wg, 256);
        issue_pv<0, 8>(c, accB, a.pb, it, 1);
        it++;
        if (next) wait_full(c, it);
        wgmma_fence();
        mma_half<0, true>(c, accA, it);
        wgmma_commit();
        bar_arrive(2 - wg, 256);
        const float r0 = quad_rcp_sum(a.l0), r1 = quad_rcp_sum(a.l1);
#pragma unroll
        for (int i = 32; i < 64; i++) t[i] = 0;
        wgmma_wait<1>();
        release(c, it - 1);
        capture_scaled<0>(t, accB, r0, r1);
        wgmma_fence();
        mma_half<1, true>(c, accB, it);
        wgmma_commit();
      } else {
        const float r0 = 0.5f * bf_lo(b0), r1 = 0.5f * bf_lo(b1);
        if (type == T_G) capture_gate<0>(t, accA, r0, r1);
        else if (ti == 0) capture_fixup<0>(t, accA, sbase + SM_CSUM + (lane & 3) * 8, s0, q0, s1, q1);
        else capture_plain<0>(t, accA);
        if (next) wait_full(c, it);
        wgmma_fence();
        mma_half<0, true>(c, accA, it);
        wgmma_commit();
        wgmma_wait<1>();
        release(c, it - 1);
        if (type == T_G) capture_gate<32>(t, accB, r0, r1);
        else if (ti == 0) capture_fixup<32>(t, accB, sbase + SM_CSUM + 512 + (lane & 3) * 8, s0, q0, s1, q1);
        else capture_plain<32>(t, accB);
        wgmma_fence();
        mma_half<1, true>(c, accB, it);
        wgmma_commit();
      }
      c.it = it;
      s0 = 0.f; s1 = 0.f; q0 = 0.f; q1 = 0.f;
      pend = is_qa ? 1 : (type == T_Z2 || type == T_Z1 || type == T_Y) ? 6 : 2;
      ptype = type;
      PROF(ti * 4 + 2);
      PROF(ti * 4 + 3);
      if (!next) {
#pragma unroll 1
        for (; pend > 0; pend--) half_store(c, t);
        break;
      }
    }
    wgmma_wait<0>();
    PROF(59);
  }
  __syncwarp();
  cluster_arrive_relaxed();
  cluster_wait();
  if (tid == 0) g_flags[F_EPOCH + blockIdx.x] += 1;
  PROFG(63);
}

typedef CUresult (*PFN_encodeTiled)(CUtensorMap*, CUtensorMapDataType, cuuint32_t, void*, const cuuint64_t*, const cuuint64_t*, const cuuint32_t*,
                                    const cuuint32_t*, CUtensorMapInterleave, CUtensorMapSwizzle, CUtensorMapL2promotion, CUtensorMapFloatOOBfill);

static void map_2d(PFN_encodeTiled enc, CUtensorMap* m, const void* ptr, uint64_t rows, uint64_t cols, uint32_t box_rows = 128) {
  cuuint64_t dims[2] = {cols, rows}; cuuint64_t strides[1] = {cols * 2};
  cuuint32_t box[2] = {64, box_rows}; cuuint32_t es[2] = {1, 1};
  enc(m, CU_TENSOR_MAP_DATA_TYPE_BFLOAT16, 2, const_cast<void*>(ptr), dims, strides, box, es, CU_TENSOR_MAP_INTERLEAVE_NONE,
      CU_TENSOR_MAP_SWIZZLE_128B, CU_TENSOR_MAP_L2_PROMOTION_L2_256B, CU_TENSOR_MAP_FLOAT_OOB_FILL_NONE);
}
static void map_3d(PFN_encodeTiled enc, CUtensorMap* m, const void* ptr, uint64_t rows, uint64_t cols) {
  cuuint64_t dims[3] = {64, rows, cols / 64}; cuuint64_t strides[2] = {cols * 2, 128};
  cuuint32_t box[3] = {64, 64, 2}; cuuint32_t es[3] = {1, 1, 1};
  enc(m, CU_TENSOR_MAP_DATA_TYPE_BFLOAT16, 3, const_cast<void*>(ptr), dims, strides, box, es, CU_TENSOR_MAP_INTERLEAVE_NONE,
      CU_TENSOR_MAP_SWIZZLE_128B, CU_TENSOR_MAP_L2_PROMOTION_L2_256B, CU_TENSOR_MAP_FLOAT_OOB_FILL_NONE);
}
static unsigned short mk(int type, int mp, int idx) { return (unsigned short)(type | (mp << 4) | (idx << 8)); }

#define SPLIT0 38
#define SPLIT1 40
#define SPLIT2 40
#define SPLIT3 37
static void build_schedule(Params& P) {
  for (int c = 0; c < NCLUSTERS; c++)
    for (int t = 0; t < MAXT + 2; t++) P.tasks[c][t] = 0;
  static const char* const plan[8] = {
      "q0 h1 q9",
      "z0 q1 h2 q12",
      "z2 q3 q7 q10",
      "z1 q2 h3 q13",
      "z4 q5 q8 q11",
      "z3 q4 h4 q14",
      "z6 h0 h6",
      "z5 q6 h5 q15"
  };
  static const int split[4] = {SPLIT0, SPLIT1, SPLIT2, SPLIT3};
  for (int mp = 0; mp < 8; mp++) {
    for (int j = 0; j < 8; j++) {
      unsigned short* T = P.tasks[mp * 8 + j];
      int n = 0;
      for (const char* q = plan[j]; *q;) {
        const char kind = *q++;
        int idx = 0;
        while (*q >= '0' && *q <= '9') idx = idx * 10 + (*q++ - '0');
        while (*q == ' ') q++;
        if (kind == 'z') T[n++] = mk(T_Z2, mp, idx);
        else if (kind == 'q') T[n++] = mk(T_QA, mp, idx);
        else { T[n++] = mk(T_Z1, mp, idx); T[n++] = mk(T_G, mp, idx); }
      }
      if (j & 1) {
        T[n++] = mk(T_S, mp, j >> 1);
        P.krange[mp * 8 + j][0] = 0; P.krange[mp * 8 + j][1] = (unsigned char)split[j >> 1];
      } else {
        T[n++] = mk(T_Y, mp, j >> 1); T[n++] = mk(T_S, mp, j >> 1);
        P.krange[mp * 8 + j][0] = (unsigned char)split[j >> 1]; P.krange[mp * 8 + j][1] = 64;
      }
    }
  }
}

extern "C" void kernel_launch(void* const* d_in, const int* in_sizes, int n_in, void* d_out, int out_size) {
  (void)in_sizes; (void)n_in; (void)out_size;
  static PFN_encodeTiled enc = nullptr;
  static void *p_xn, *p_z2, *p_o, *p_h, *p_sy;
  if (!enc) {
    void* fn = nullptr; cudaDriverEntryPointQueryResult qr;
    cudaGetDriverEntryPoint("cuTensorMapEncodeTiled", &fn, cudaEnableDefault, &qr);
    enc = (PFN_encodeTiled)fn;
    cudaGetSymbolAddress(&p_xn, g_xn); cudaGetSymbolAddress(&p_z2, g_z2); cudaGetSymbolAddress(&p_o, g_o);
    cudaGetSymbolAddress(&p_h, g_h); cudaGetSymbolAddress(&p_sy, g_sy);
    cudaFuncSetAttribute(mega_kernel, cudaFuncAttributeMaxDynamicSharedMemorySize, SMEM_BYTES);
  }
  Params P;
  map_2d(enc, &P.maps[M_XN], p_xn, SEQ, DM);
  map_2d(enc, &P.maps[M_WSP], d_in[7], SEQ, SEQ);
  map_2d(enc, &P.maps[M_O_LD], p_o, SEQ, HD);
  map_2d(enc, &P.maps[M_H_LD], p_h, SEQ, FH);
  map_2d(enc, &P.maps[M_X], d_in[0], SEQ, DM);
  map_2d(enc, &P.maps[M_SY_LD], p_sy, SEQ, DM);
  map_2d(enc, &P.maps[M_K], d_in[1], 4 * SK, 128);
  map_2d(enc, &P.maps[M_V], d_in[2], 4 * SK, 128);
  map_3d(enc, &P.maps[M_WIN], d_in[6], DM, FF);
  map_3d(enc, &P.maps[M_WQ], d_in[3], DM, HD);
  map_3d(enc, &P.maps[M_Z2], p_z2, SEQ, FH);
  map_3d(enc, &P.maps[M_WO], d_in[4], HD, DM);
  map_3d(enc, &P.maps[M_WOUT], d_in[9], FH, DM);
  map_2d(enc, &P.maps[M_Z2_ST], p_z2, SEQ, FH, 64);
  map_2d(enc, &P.maps[M_O_ST], p_o, SEQ, HD, 64);
  map_2d(enc, &P.maps[M_H_ST], p_h, SEQ, FH, 64);
  map_2d(enc, &P.maps[M_SY_ST], p_sy, SEQ, DM, 64);
  map_2d(enc, &P.maps[M_OUT], d_out, SEQ, DM, 64);
  P.x = (const bf16*)d_in[0];
  P.out = (bf16*)d_out;
  P.b_sp = (const bf16*)d_in[8];
  P.kv[0] = (const bf16*)d_in[1];
  P.kv[1] = (const bf16*)d_in[2];
  P.one = 1;
  build_schedule(P);
  mega_kernel<<<NCLUSTERS * 2, 384, SMEM_BYTES, cudaStreamPerThread>>>(P);
}
```

```cpp
#include <cuda_runtime.h>
#include <cuda_bf16.h>
#include <cuda.h>
#include <stdint.h>

typedef __nv_bfloat16 bf16;

constexpr int SEQ = 2048, DM = 1024, HD = 4096, FF = 3584, FH = 1792, SK = 2048, WIN = 512;
constexpr int NCLUSTERS = 64;
constexpr int MAXT = 10;
#define LN_PERIOD 3
#define X_DELAY 0
#define LN_DELAY 2

__device__ bf16 g_xn[SEQ * DM];
__device__ bf16 g_z2[SEQ * FH];
__device__ bf16 g_o[SEQ * HD];
__device__ bf16 g_h[SEQ * FH];
__device__ bf16 g_sy[SEQ * DM];
constexpr int F_XN = 0;
constexpr int F_Z2N = 16;
constexpr int F_O = 64;
constexpr int F_H = 576;
constexpr int F_SY = 704;
constexpr int F_EPOCH = 768;
constexpr int F_COUNT = 1024;
__device__ __align__(16) unsigned int g_flags[F_COUNT];
__device__ float2 g_xstat[SEQ];
__device__ ulonglong2 g_csum[8 * 16 * 64];
__device__ __align__(16) unsigned long long g_stats[8 * SEQ];

enum { M_XN = 0, M_WSP, M_O_LD, M_H_LD, M_X, M_SY_LD, M_K, M_V,
       M_WIN, M_WQ, M_Z2, M_WO, M_WOUT,
       M_Z2_ST, M_O_ST, M_H_ST, M_SY_ST, M_OUT,
       M_COUNT };
enum { T_NONE = 0, T_Z2, T_QA, T_Z1, T_G, T_Y, T_S };

struct Params {
  CUtensorMap maps[M_COUNT];
  const bf16* x;
  bf16* out;
  const bf16* b_sp;
  const bf16* kv[2];
  int one;
  unsigned short tasks[NCLUSTERS][MAXT + 2];
  unsigned char krange[NCLUSTERS][2];
};

constexpr int STAGES = 4;
constexpr int STAGE_BYTES = 49152;
constexpr int SM_STG = STAGES * STAGE_BYTES;
constexpr int SM_BAR = SM_STG + 32768;
constexpr int SM_STAT = SM_BAR + 256;
constexpr int SM_CSUM = SM_STAT + 1024;
constexpr int SMEM_BYTES = SM_CSUM + 1024;

template <int TB>
__device__ __forceinline__ void wgmma_ss_n128(float (&d)[64], uint32_t alo, uint32_t blo, int scale_d) {
  asm volatile("{\n.reg .pred p;\n.reg .b64 da, db;\n.reg .b32 hi;\nmov.b32 hi, 0x40000040;\nmov.b64 da, {%64, hi};\nmov.b64 db, {%65, hi};\n"
    "setp.ne.b32 p, %66, 0;\n"
    "wgmma.mma_async.sync.aligned.m64n128k16.f32.bf16.bf16 {%0, %1, %2, %3, %4, %5, %6, %7, %8, %9, %10, %11, %12, %13, %14, %15, %16, %17, %18, %19, %20, %21, %22, %23, %24, %25, %26, %27, %28, %29, %30, %31, %32, %33, %34, %35, %36, %37, %38, %39, %40, %41, %42, %43, %44, %45, %46, %47, %48, %49, %50, %51, %52, %53, %54, %55, %56, %57, %58, %59, %60, %61, %62, %63}, da, db, p, 1, 1, 0, %67;\n}\n"
    : "+f"(d[0]), "+f"(d[1]), "+f"(d[2]), "+f"(d[3]), "+f"(d[4]), "+f"(d[5]), "+f"(d[6]), "+f"(d[7]), "+f"(d[8]), "+f"(d[9]), "+f"(d[10]), "+f"(d[11]), "+f"(d[12]), "+f"(d[13]), "+f"(d[14]), "+f"(d[15]), "+f"(d[16]), "+f"(d[17]), "+f"(d[18]), "+f"(d[19]), "+f"(d[20]), "+f"(d[21]), "+f"(d[22]), "+f"(d[23]), "+f"(d[24]), "+f"(d[25]), "+f"(d[26]), "+f"(d[27]), "+f"(d[28]), "+f"(d[29]), "+f"(d[30]), "+f"(d[31]), "+f"(d[32]), "+f"(d[33]), "+f"(d[34]), "+f"(d[35]), "+f"(d[36]), "+f"(d[37]), "+f"(d[38]), "+f"(d[39]), "+f"(d[40]), "+f"(d[41]), "+f"(d[42]), "+f"(d[43]), "+f"(d[44]), "+f"(d[45]), "+f"(d[46]), "+f"(d[47]), "+f"(d[48]), "+f"(d[49]), "+f"(d[50]), "+f"(d[51]), "+f"(d[52]), "+f"(d[53]), "+f"(d[54]), "+f"(d[55]), "+f"(d[56]), "+f"(d[57]), "+f"(d[58]), "+f"(d[59]), "+f"(d[60]), "+f"(d[61]), "+f"(d[62]), "+f"(d[63])
    : "r"(alo), "r"(blo), "r"(scale_d), "n"(TB));
}
__device__ __forceinline__ void wgmma_ss_n256(float (&d)[64], float (&e)[64], uint32_t alo, uint32_t blo, int scale_d) {
  asm volatile("{\n.reg .pred p;\n.reg .b64 da, db;\n.reg .b32 hi;\nmov.b32 hi, 0x40000040;\nmov.b64 da, {%128, hi};\nmov.b64 db, {%129, hi};\n"
    "setp.ne.b32 p, %130, 0;\n"
    "wgmma.mma_async.sync.aligned.m64n256k16.f32.bf16.bf16 {%0, %1, %2, %3, %4, %5, %6, %7, %8, %9, %10, %11, %12, %13, %14, %15, %16, %17, %18, %19, %20, %21, %22, %23, %24, %25, %26, %27, %28, %29, %30, %31, %32, %33, %34, %35, %36, %37, %38, %39, %40, %41, %42, %43, %44, %45, %46, %47, %48, %49, %50, %51, %52, %53, %54, %55, %56, %57, %58, %59, %60, %61, %62, %63, %64, %65, %66, %67, %68, %69, %70, %71, %72, %73, %74, %75, %76, %77, %78, %79, %80, %81, %82, %83, %84, %85, %86, %87, %88, %89, %90, %91, %92, %93, %94, %95, %96, %97, %98, %99, %100, %101, %102, %103, %104, %105, %106, %107, %108, %109, %110, %111, %112, %113, %114, %115, %116, %117, %118, %119, %120, %121, %122, %123, %124, %125, %126, %127}, da, db, p, 1, 1, 0, 1;\n}\n"
    : "+f"(d[0]), "+f"(d[1]), "+f"(d[2]), "+f"(d[3]), "+f"(d[4]), "+f"(d[5]), "+f"(d[6]), "+f"(d[7]), "+f"(d[8]), "+f"(d[9]), "+f"(d[10]), "+f"(d[11]), "+f"(d[12]), "+f"(d[13]), "+f"(d[14]), "+f"(d[15]), "+f"(d[16]), "+f"(d[17]), "+f"(d[18]), "+f"(d[19]), "+f"(d[20]), "+f"(d[21]), "+f"(d[22]), "+f"(d[23]), "+f"(d[24]), "+f"(d[25]), "+f"(d[26]), "+f"(d[27]), "+f"(d[28]), "+f"(d[29]), "+f"(d[30]), "+f"(d[31]), "+f"(d[32]), "+f"(d[33]), "+f"(d[34]), "+f"(d[35]), "+f"(d[36]), "+f"(d[37]), "+f"(d[38]), "+f"(d[39]), "+f"(d[40]), "+f"(d[41]), "+f"(d[42]), "+f"(d[43]), "+f"(d[44]), "+f"(d[45]), "+f"(d[46]), "+f"(d[47]), "+f"(d[48]), "+f"(d[49]), "+f"(d[50]), "+f"(d[51]), "+f"(d[52]), "+f"(d[53]), "+f"(d[54]), "+f"(d[55]), "+f"(d[56]), "+f"(d[57]), "+f"(d[58]), "+f"(d[59]), "+f"(d[60]), "+f"(d[61]), "+f"(d[62]), "+f"(d[63]), "+f"(e[0]), "+f"(e[1]), "+f"(e[2]), "+f"(e[3]), "+f"(e[4]), "+f"(e[5]), "+f"(e[6]), "+f"(e[7]), "+f"(e[8]), "+f"(e[9]), "+f"(e[10]), "+f"(e[11]), "+f"(e[12]), "+f"(e[13]), "+f"(e[14]), "+f"(e[15]), "+f"(e[16]), "+f"(e[17]), "+f"(e[18]), "+f"(e[19]), "+f"(e[20]), "+f"(e[21]), "+f"(e[22]), "+f"(e[23]), "+f"(e[24]), "+f"(e[25]), "+f"(e[26]), "+f"(e[27]), "+f"(e[28]), "+f"(e[29]), "+f"(e[30]), "+f"(e[31]), "+f"(e[32]), "+f"(e[33]), "+f"(e[34]), "+f"(e[35]), "+f"(e[36]), "+f"(e[37]), "+f"(e[38]), "+f"(e[39]), "+f"(e[40]), "+f"(e[41]), "+f"(e[42]), "+f"(e[43]), "+f"(e[44]), "+f"(e[45]), "+f"(e[46]), "+f"(e[47]), "+f"(e[48]), "+f"(e[49]), "+f"(e[50]), "+f"(e[51]), "+f"(e[52]), "+f"(e[53]), "+f"(e[54]), "+f"(e[55]), "+f"(e[56]), "+f"(e[57]), "+f"(e[58]), "+f"(e[59]), "+f"(e[60]), "+f"(e[61]), "+f"(e[62]), "+f"(e[63])
    : "r"(alo), "r"(blo), "r"(scale_d));
}

__device__ __forceinline__ uint32_t smem_u32(const void* p) { return (uint32_t)__cvta_generic_to_shared(p); }
__device__ __forceinline__ void mbar_init(uint32_t bar, uint32_t cnt) { asm volatile("mbarrier.init.shared::cta.b64 [%0], %1;" ::"r"(bar), "r"(cnt) : "memory"); }
__device__ __forceinline__ void mbar_expect_tx(uint32_t bar, uint32_t bytes) { asm volatile("mbarrier.arrive.expect_tx.shared::cta.b64 _, [%0], %1;" ::"r"(bar), "r"(bytes) : "memory"); }
__device__ __forceinline__ void mbar_arrive(uint32_t bar) { asm volatile("mbarrier.arrive.shared::cta.b64 _, [%0];" ::"r"(bar) : "memory"); }
__device__ __forceinline__ void mbar_wait(uint32_t bar, uint32_t parity) {
  asm volatile(
      "{\n.reg .pred p;\n.reg .u32 n;\nmov.u32 n, 0;\n"
      "LAB_WAIT:\nmbarrier.try_wait.parity.shared::cta.b64 p, [%0], %1;\n@p bra LAB_DONE;\n"
      "add.u32 n, n, 1;\nsetp.lt.u32 p, n, 4194304;\n@p bra LAB_WAIT;\ntrap;\nLAB_DONE:\n}\n" ::"r"(bar), "r"(parity) : "memory");
}
__device__ __forceinline__ void mbar_wait_idle(uint32_t bar, uint32_t parity) {
  asm volatile(
      "{\n.reg .pred p;\n.reg .u32 n;\nmov.u32 n, 0;\n"
      "LAB_WAIT:\nmbarrier.try_wait.parity.shared::cta.b64 p, [%0], %1, 1000;\n@p bra LAB_DONE;\n"
      "add.u32 n, n, 1;\nsetp.lt.u32 p, n, 4194304;\n@p bra LAB_WAIT;\ntrap;\nLAB_DONE:\n}\n" ::"r"(bar), "r"(parity) : "memory");
}
__device__ __forceinline__ bool mbar_test2(uint32_t bar0, uint32_t par0, uint32_t bar1, uint32_t par1) {
  uint32_t ok;
  asm volatile("{\n.reg .pred p, q;\nmbarrier.test_wait.parity.shared::cta.b64 p, [%1], %2;\nmbarrier.test_wait.parity.shared::cta.b64 q, [%3], %4;\n"
               "and.pred p, p, q;\nvote.sync.all.pred p, p, 0xffffffff;\nselp.u32 %0, 1, 0, p;\n}\n" : "=r"(ok) : "r"(bar0), "r"(par0), "r"(bar1), "r"(par1) : "memory");
  return ok != 0;
}
__device__ __forceinline__ void tma_load_2d(uint32_t dst, const CUtensorMap* tm, uint32_t bar, int c0, int c1) {
  asm volatile("cp.async.bulk.tensor.2d.shared::cluster.global.mbarrier::complete_tx::bytes [%0], [%1, {%3, %4}], [%2];" ::"r"(dst), "l"(tm), "r"(bar), "r"(c0), "r"(c1) : "memory");
}
__device__ __forceinline__ void tma_load_2d_mc(uint32_t dst, const CUtensorMap* tm, uint32_t bar, int c0, int c1) {
  asm volatile("cp.async.bulk.tensor.2d.shared::cluster.global.mbarrier::complete_tx::bytes.multicast::cluster [%0], [%1, {%3, %4}], [%2], %5;" ::"r"(dst), "l"(tm), "r"(bar), "r"(c0), "r"(c1), "h"((uint16_t)3) : "memory");
}
__device__ __forceinline__ void tma_load_3d_mc(uint32_t dst, const CUtensorMap* tm, uint32_t bar, int row, int chunk) {
  asm volatile("cp.async.bulk.tensor.3d.shared::cluster.global.mbarrier::complete_tx::bytes.multicast::cluster [%0], [%1, {%3, %4, %5}], [%2], %6;" ::"r"(dst), "l"(tm), "r"(bar), "r"(0), "r"(row), "r"(chunk), "h"((uint16_t)3) : "memory");
}
__device__ __forceinline__ void tma_load_3d(uint32_t dst, const CUtensorMap* tm, uint32_t bar, int row, int chunk) {
  asm volatile("cp.async.bulk.tensor.3d.shared::cluster.global.mbarrier::complete_tx::bytes [%0], [%1, {%3, %4, %5}], [%2];" ::"r"(dst), "l"(tm), "r"(bar), "r"(0), "r"(row), "r"(chunk) : "memory");
}
__device__ __forceinline__ void tma_store_2d(const CUtensorMap* tm, uint32_t src, int col, int row) {
  asm volatile("cp.async.bulk.tensor.2d.global.shared::cta.bulk_group [%0, {%2, %3}], [%1];" ::"l"(tm), "r"(src), "r"(col), "r"(row) : "memory");
}
__device__ __forceinline__ void wgmma_fence() { asm volatile("wgmma.fence.sync.aligned;" ::: "memory"); }
__device__ __forceinline__ void wgmma_commit() { asm volatile("wgmma.commit_group.sync.aligned;" ::: "memory"); }
template <int N> __device__ __forceinline__ void wgmma_wait() { asm volatile("wgmma.wait_group.sync.aligned %0;" ::"n"(N) : "memory"); }
__device__ __forceinline__ void fence_async() { asm volatile("fence.proxy.async.global;" ::: "memory"); }
__device__ __forceinline__ void fence_async_smem() { asm volatile("fence.proxy.async.shared::cta;" ::: "memory"); }
__device__ __forceinline__ void cluster_arrive() { asm volatile("barrier.cluster.arrive.release;" ::: "memory"); }
__device__ __forceinline__ void cluster_arrive_relaxed() { asm volatile("barrier.cluster.arrive.relaxed;" ::: "memory"); }
__device__ __forceinline__ void cluster_wait() { asm volatile("barrier.cluster.wait.acquire;" ::: "memory"); }
__device__ __forceinline__ void bar_sync(int id, int n) { asm volatile("bar.sync %0, %1;" ::"r"(id), "r"(n) : "memory"); }
__device__ __forceinline__ void bar_arrive(int id, int n) { asm volatile("bar.arrive %0, %1;" ::"r"(id), "r"(n) : "memory"); }
__device__ __forceinline__ uint32_t ld_relaxed(const unsigned int* p) {
  uint32_t v; asm volatile("ld.relaxed.gpu.global.u32 %0, [%1];" : "=r"(v) : "l"(p) : "memory"); return v;
}
__device__ __forceinline__ void fence_acquire() { asm volatile("fence.acquire.gpu;" ::: "memory"); }
__device__ __forceinline__ void red_release(unsigned int* p) { asm volatile("red.release.gpu.global.add.u32 [%0], 1;" ::"l"(p) : "memory"); }
__device__ __forceinline__ uint32_t launch_epoch() { return ld_relaxed(&g_flags[F_EPOCH + blockIdx.x]) + 1; }
__device__ __forceinline__ void flag_wait(int idx, uint32_t target) {
  uint32_t n = 0;
  target *= launch_epoch();
  while ((int)(ld_relaxed(&g_flags[idx]) - target) < 0) {
    __nanosleep(20);
    if (++n > (1u << 22)) __trap();
  }
  fence_acquire();
}
__device__ __forceinline__ uint32_t pack_bf16(float lo, float hi) {
  uint32_t r; asm("cvt.rn.bf16x2.f32 %0, %1, %2;" : "=r"(r) : "f"(hi), "f"(lo)); return r;
}
__device__ __forceinline__ float bf_lo(uint32_t v) { return __uint_as_float(v << 16); }
__device__ __forceinline__ float bf_hi(uint32_t v) { return __uint_as_float(v & 0xffff0000u); }
__device__ __forceinline__ float ex2(float x) { float r; asm("ex2.approx.ftz.f32 %0, %1;" : "=f"(r) : "f"(x)); return r; }
__device__ __forceinline__ float tanh_fast(float x) { float r; asm("tanh.approx.f32 %0, %1;" : "=f"(r) : "f"(x)); return r; }
__device__ __forceinline__ float gelu2_tanh(float x) {
  float u = x * fmaf(x * x, 0.0356774081f, 0.7978845608f);
  return fmaf(x, tanh_fast(u), x);
}
__device__ __forceinline__ uint32_t mul_bf2(uint32_t a, uint32_t b) { uint32_t r; asm("mul.rn.bf16x2 %0, %1, %2;" : "=r"(r) : "r"(a), "r"(b)); return r; }
__device__ __forceinline__ uint32_t fma_bf2(uint32_t a, uint32_t b, uint32_t c) { uint32_t r; asm("fma.rn.bf16x2 %0, %1, %2, %3;" : "=r"(r) : "r"(a), "r"(b), "r"(c)); return r; }
__device__ __forceinline__ float silu(float y) {
  float r; asm("rcp.approx.ftz.f32 %0, %1;" : "=f"(r) : "f"(1.0f + ex2(-1.4426950409f * y)));
  return y * r;
}
__device__ __forceinline__ void stmatrix_x4(uint32_t addr, uint32_t r0, uint32_t r1, uint32_t r2, uint32_t r3) {
  asm volatile("stmatrix.sync.aligned.m8n8.x4.shared.b16 [%0], {%1, %2, %3, %4};" ::"r"(addr), "r"(r0), "r"(r1), "r"(r2), "r"(r3) : "memory");
}
__device__ __forceinline__ void ldmatrix_x4(uint32_t addr, uint32_t& r0, uint32_t& r1, uint32_t& r2, uint32_t& r3) {
  asm volatile("ldmatrix.sync.aligned.m8n8.x4.shared.b16 {%0, %1, %2, %3}, [%4];" : "=r"(r0), "=r"(r1), "=r"(r2), "=r"(r3) : "r"(addr) : "memory");
}

#define PROF(slot)
#define PROFT(slot, thr)
#define PROFG(slot)

struct Ctx {
  uint32_t sbase;
  uint32_t d16;
  uint32_t rel;
  uint32_t bars;
  uint32_t it;
  uint32_t sc;
  uint32_t stg;
  uint32_t st_off;
  uint32_t st_sw;
  int wg, t;
  int one;
};
__device__ __forceinline__ uint32_t stage_addr(const Ctx& c, uint32_t it) { return c.sbase + (it & 3) * STAGE_BYTES; }
__device__ __forceinline__ void wait_full(const Ctx& c, uint32_t it) { mbar_wait(c.bars + 8 * (it & 3), (it >> 2) & 1); }
__device__ __forceinline__ void release(const Ctx& c, uint32_t it) {
  if (c.t < 2) asm volatile("mbarrier.arrive.shared::cluster.b64 _, [%0];" ::"r"(c.rel + 8 * (it & 3)) : "memory");
}
__device__ __forceinline__ uint32_t desc_lo(const Ctx& c, uint32_t addr, uint32_t lbo) { return (addr >> 4) - c.d16 + ((lbo >> 4) << 16); }
template <bool INIT>
__device__ __forceinline__ void mma_step(const Ctx& c, float (&accA)[64], float (&accB)[64], uint32_t it) {
  const uint32_t st = desc_lo(c, c.sbase, 0) + (it & 3) * (STAGE_BYTES >> 4);
  const uint32_t da = st + c.wg * 512 + (1 << 16), db = st + 1024 + (512 << 16);
  wgmma_fence();
#pragma unroll
  for (int kk = 0; kk < 4; kk++) wgmma_ss_n256(accA, accB, da + kk * 2, db + kk * 128, (INIT && kk == 0) ? 0 : 1);
  wgmma_commit();
}
__device__ __forceinline__ void stg_acquire(const Ctx& c) { mbar_wait(c.bars + 80 + c.wg * 8, (c.sc & 1) ^ 1); }
__device__ __forceinline__ void stg_commit(Ctx& c) {
  __syncwarp();
  if ((c.t & 31) == 0) mbar_arrive(c.bars + 64 + c.wg * 8);
  c.sc++;
}
template <int OFF>
__device__ __forceinline__ void box_write(const Ctx& c, uint32_t base, const uint32_t (&t)[64]) {
#pragma unroll
  for (int kk = 0; kk < 4; kk++)
    stmatrix_x4(base + c.st_off + (((kk * 2) ^ c.st_sw) << 4), t[OFF + 4 * kk], t[OFF + 4 * kk + 1], t[OFF + 4 * kk + 2], t[OFF + 4 * kk + 3]);
}
__device__ __forceinline__ void acc_write(const Ctx& c, uint32_t base, const float (&s)[64]) {
#pragma unroll
  for (int kk = 0; kk < 8; kk++)
    stmatrix_x4(base + (kk >> 2) * 8192 + c.st_off + ((((kk & 3) * 2) ^ c.st_sw) << 4), pack_bf16(s[8 * kk], s[8 * kk + 1]),
                pack_bf16(s[8 * kk + 2], s[8 * kk + 3]), pack_bf16(s[8 * kk + 4], s[8 * kk + 5]), pack_bf16(s[8 * kk + 6], s[8 * kk + 7]));
}
__device__ __forceinline__ uint32_t opaque(uint32_t v) { asm volatile("" : "+r"(v)); return v; }
__device__ __forceinline__ void half_store(Ctx& c, uint32_t (&t)[64]) {
  stg_acquire(c);
  const uint32_t stg = opaque(c.stg);
  box_write<0>(c, stg, t);
  box_write<16>(c, stg + 8192, t);
  fence_async_smem();
  stg_commit(c);
#pragma unroll
  for (int i = 0; i < 32; i++) asm volatile("mov.b32 %0, %1;" : "=r"(t[i]) : "r"(t[i + 32]));
}
__device__ __forceinline__ void final_half(const Ctx& c, const float (&acc)[64], uint32_t a, uint32_t pitch, const CUtensorMap* m, int col, int row) {
  uint32_t g[32];
#pragma unroll
  for (int kk = 0; kk < 8; kk++)
    ldmatrix_x4(a + (kk >> 2) * pitch + c.st_off + ((((kk & 3) * 2) ^ c.st_sw) << 4), g[4 * kk], g[4 * kk + 1], g[4 * kk + 2], g[4 * kk + 3]);
#pragma unroll
  for (int i = 0; i < 32; i++) g[i] = pack_bf16(acc[2 * i] * bf_lo(g[i]), acc[2 * i + 1] * bf_hi(g[i]));
#pragma unroll
  for (int kk = 0; kk < 8; kk++)
    stmatrix_x4(a + (kk >> 2) * pitch + c.st_off + ((((kk & 3) * 2) ^ c.st_sw) << 4), g[4 * kk], g[4 * kk + 1], g[4 * kk + 2], g[4 * kk + 3]);
  fence_async_smem();
  bar_sync(3 + c.wg, 128);
  if (c.t == 0) {
    fence_async();
    asm volatile("cp.reduce.async.bulk.tensor.2d.global.shared::cta.add.bulk_group [%0, {%2, %3}], [%1];" ::"l"(m), "r"(a), "r"(col), "r"(row) : "memory");
    asm volatile("cp.reduce.async.bulk.tensor.2d.global.shared::cta.add.bulk_group [%0, {%2, %3}], [%1];" ::"l"(m), "r"(a + pitch), "r"(col + 64), "r"(row) : "memory");
    asm volatile("cp.async.bulk.commit_group;" ::: "memory");
  }
}
__device__ __forceinline__ void rotate16(uint32_t (&t)[64]) {
#pragma unroll
  for (int i = 0; i < 16; i++)
    asm volatile("{\n.reg .b32 v;\nmov.b32 v, %0;\nmov.b32 %0, %1;\nmov.b32 %1, %2;\nmov.b32 %2, %3;\nmov.b32 %3, v;\n}\n"
                 : "+r"(t[i]), "+r"(t[i + 16]), "+r"(t[i + 32]), "+r"(t[i + 48]));
}
__device__ __forceinline__ float quad_rcp_sum(float l) {
  l += __shfl_xor_sync(0xffffffffu, l, 1);
  l += __shfl_xor_sync(0xffffffffu, l, 2);
  float r; asm("rcp.approx.ftz.f32 %0, %1;" : "=f"(r) : "f"(l));
  return r;
}
template <int OFF>
__device__ __forceinline__ void capture_plain(uint32_t (&d)[64], const float (&s)[64]) {
#pragma unroll
  for (int i = 0; i < 32; i++) d[OFF + i] = pack_bf16(s[2 * i], s[2 * i + 1]);
}
template <int OFF>
__device__ __forceinline__ void capture_scaled(uint32_t (&d)[64], const float (&s)[64], float r0, float r1) {
#pragma unroll
  for (int i = 0; i < 32; i++) { const float r = (i & 1) ? r1 : r0; d[OFF + i] = pack_bf16(s[2 * i] * r, s[2 * i + 1] * r); }
}
template <int OFF>
__device__ __forceinline__ void capture_gate(uint32_t (&d)[64], const float (&s)[64], float b0, float b1) {
#pragma unroll
  for (int i = 0; i < 32; i++) {
    const float b = (i & 1) ? b1 : b0;
    d[OFF + i] = mul_bf2(pack_bf16(fmaf(s[2 * i], 0.5f, b), fmaf(s[2 * i + 1], 0.5f, b)), d[OFF + i]);
  }
}
template <int K0, int K1>
__device__ __forceinline__ void issue_qk(const Ctx& c, float (&s)[64], uint32_t qaddr, uint32_t it) {
  const uint32_t da = desc_lo(c, qaddr, 16), db = desc_lo(c, c.sbase, 16) + (it & 3) * (STAGE_BYTES >> 4);
  wgmma_fence();
#pragma unroll
  for (int kk = K0; kk < K1; kk++) wgmma_ss_n128<0>(s, da + (kk >> 2) * 512 + (kk & 3) * 2, db + (kk >> 2) * 1024 + (kk & 3) * 2, kk == 0 ? 0 : 1);
  wgmma_commit();
}
template <int K0, int K1>
__device__ __forceinline__ void issue_pv(const Ctx& c, float (&o)[64], uint32_t paddr, uint32_t it, int first_scale) {
  const uint32_t da = desc_lo(c, paddr, 16), db = desc_lo(c, c.sbase, 16384) + (it & 3) * (STAGE_BYTES >> 4);
  wgmma_fence();
#pragma unroll
  for (int kk = K0; kk < K1; kk++) wgmma_ss_n128<1>(o, da + (kk >> 2) * 512 + (kk & 3) * 2, db + kk * 128, kk == 0 ? first_scale : 1);
  wgmma_commit();
}
constexpr float SM_SCALE = 0.08838834764831845f * 1.4426950408889634f;
__device__ __forceinline__ void row_max(const float (&s)[64], int t0, int t1, float& x0, float& x1) {
  t0 = max(t0, __shfl_xor_sync(0xffffffffu, t0, 1)); t1 = max(t1, __shfl_xor_sync(0xffffffffu, t1, 1));
  t0 = max(t0, __shfl_xor_sync(0xffffffffu, t0, 2)); t1 = max(t1, __shfl_xor_sync(0xffffffffu, t1, 2));
  if (__any_sync(0xffffffffu, t0 == 0 || t1 == 0)) {
    uint32_t u0 = 0xffffffffu, u1 = 0xffffffffu;
#pragma unroll
    for (int i = 0; i < 64; i += 4) {
      u0 = __vimin3_u32(u0, __float_as_uint(s[i]), __float_as_uint(s[i + 1]));
      u1 = __vimin3_u32(u1, __float_as_uint(s[i + 2]), __float_as_uint(s[i + 3]));
    }
    u0 = min(u0, __shfl_xor_sync(0xffffffffu, u0, 1)); u1 = min(u1, __shfl_xor_sync(0xffffffffu, u1, 1));
    u0 = min(u0, __shfl_xor_sync(0xffffffffu, u0, 2)); u1 = min(u1, __shfl_xor_sync(0xffffffffu, u1, 2));
    if (t0 == 0) t0 = (int)u0;
    if (t1 == 0) t1 = (int)u1;
  }
  x0 = __int_as_float(t0); x1 = __int_as_float(t1);
}
struct Att {
  float n0, n1, l0, l1, r0, r1;
  uint32_t it, pb, qb;
  bool rescale, landed;
};
template <int K0, int K1, int C0, int C1>
__device__ __forceinline__ void prob_part(const float (&s)[64], Att& a, const float (&sn)[64], int (&top)[2], uint32_t (&pk)[32]) {
#pragma unroll
  for (int kk = K0; kk < K1; kk++) {
    float e[8];
#pragma unroll
    for (int i = 0; i < 8; i++) asm volatile("ex2.approx.ftz.f32 %0, %1;" : "=f"(e[i]) : "f"(fmaf(s[8 * kk + i], SM_SCALE, (i & 2) ? a.n1 : a.n0)));
    a.l0 += (e[0] + e[1]) + (e[4] + e[5]);
    a.l1 += (e[2] + e[3]) + (e[6] + e[7]);
#pragma unroll
    for (int i = 0; i < 4; i++) asm volatile("cvt.rn.bf16x2.f32 %0, %1, %2;" : "=r"(pk[4 * kk + i]) : "f"(e[2 * i + 1]), "f"(e[2 * i]));
  }
#pragma unroll
  for (int i = 8 * C0; i < 8 * C1; i += 2)
    top[(i >> 1) & 1] = __vimax3_s32(top[(i >> 1) & 1], __float_as_int(sn[i]), __float_as_int(sn[i + 1]));
  asm volatile("" : "+f"(a.l0), "+f"(a.l1), "+r"(top[0]), "+r"(top[1]));
}
#define AS1 2
#define AS2 7
#define ONCE(body) { int rep_ = 0; _Pragma("unroll 1") do { body; } while (++rep_ < c.one); }
template <int MODE, bool ODD>
__device__ __forceinline__ void att_step(Ctx& c, Att& a, int j, float (&s)[64], float (&sn)[64], float (&o)[64]) {
  int top[2] = {0, 0};
  uint32_t pk[32];
  const uint32_t itk = a.it + 1, itv = a.it + (MODE == 1 ? 2 : 1);
  a.it = itv;
  if (MODE != 0) {
    if (!a.landed) {
      if (MODE == 1) wait_full(c, itk);
      wait_full(c, itv);
    }
    fence_async_smem();
    if (MODE == 1 && ODD && j == 5) stg_commit(c);
    bar_sync(1 + c.wg, 256);
    if (MODE == 1) ONCE((issue_qk<0, 8>(c, sn, j < 3 ? c.stg : a.qb, itk)))
    else ONCE((issue_pv<0, 8>(c, o, a.pb, itv, 1), bar_arrive(2 - c.wg, 256)));
  }
  prob_part<0, AS1, 0, 0>(s, a, sn, top, pk);
  if (MODE == 1) ONCE((issue_pv<0, 8>(c, o, a.pb, itv, (j - 1) & 3), bar_arrive(2 - c.wg, 256)));
  prob_part<AS1, AS2, 0, 0>(s, a, sn, top, pk);
  ONCE(wgmma_wait<0>());
  if (MODE == 1) release(c, itk);
  release(c, itv);
  if (MODE == 0) wait_full(c, itv + 1 + c.wg);
  if (MODE == 1 && !ODD && j == 6) { stg_acquire(c); a.pb = c.stg; }
#pragma unroll
  for (int kk = 0; kk < AS2; kk++)
    stmatrix_x4(a.pb + (kk >> 2) * 8192 + c.st_off + ((((kk & 3) * 2) ^ c.st_sw) << 4), pk[4 * kk], pk[4 * kk + 1], pk[4 * kk + 2], pk[4 * kk + 3]);
  if (MODE != 2) a.landed = mbar_test2(c.bars + 8 * ((itv + 1) & 3), ((itv + 1) >> 2) & 1, c.bars + 8 * ((itv + 2) & 3), ((itv + 2) >> 2) & 1);
  prob_part<AS2, 8, 0, MODE == 2 ? 0 : 8>(s, a, sn, top, pk);
#pragma unroll
  for (int kk = AS2; kk < 8; kk++)
    stmatrix_x4(a.pb + (kk >> 2) * 8192 + c.st_off + ((((kk & 3) * 2) ^ c.st_sw) << 4), pk[4 * kk], pk[4 * kk + 1], pk[4 * kk + 2], pk[4 * kk + 3]);
  const float t0 = (16.f - a.n0) * (1.f / SM_SCALE), t1 = (16.f - a.n1) * (1.f / SM_SCALE);
  const bool over = MODE != 2 && __any_sync(0xffffffffu, top[0] > __float_as_int(t0) || top[1] > __float_as_int(t1));
  if (MODE != 0 && a.rescale) {
#pragma unroll
    for (int i = 0; i < 16; i++) { o[4 * i] *= a.r0; o[4 * i + 1] *= a.r0; o[4 * i + 2] *= a.r1; o[4 * i + 3] *= a.r1; }
    a.rescale = false;
  }
  if (MODE == 1 && !ODD && j == 4) acc_write(c, c.stg, o);
  if (MODE != 2 && ((ODD && j == 3) || over)) {
    float x0, x1;
    row_max(sn, top[0], top[1], x0, x1);
    x0 *= -SM_SCALE; x1 *= -SM_SCALE;
    if (ODD && j == 3) {
      a.r0 = quad_rcp_sum(a.l0); a.r1 = quad_rcp_sum(a.l1);
      a.l0 = 0.f; a.l1 = 0.f;
    } else {
      x0 = fminf(x0, a.n0); x1 = fminf(x1, a.n1);
      a.r0 = ex2(x0 - a.n0); a.r1 = ex2(x1 - a.n1);
      a.l0 *= a.r0; a.l1 *= a.r1;
    }
    a.n0 = x0; a.n1 = x1;
    a.rescale = true;
  }
}

__device__ __forceinline__ void ln_stats(uint32_t (&t)[64], float& r0, float& b0, float& r1, float& b1, uint32_t zero) {
  float m0 = 0.f, m1 = 0.f;
#pragma unroll
  for (int i = 0; i < 16; i++) { m0 += bf_lo(t[i]) + bf_hi(t[i]); m1 += bf_lo(t[16 + i]) + bf_hi(t[16 + i]); }
#pragma unroll
  for (int o = 16; o > 0; o >>= 1) { m0 += __shfl_xor_sync(0xffffffffu, m0, o); m1 += __shfl_xor_sync(0xffffffffu, m1, o); }
  m0 *= 1.0f / DM; m1 *= 1.0f / DM;
#pragma unroll
  for (int i = 0; i < 32; i++) asm volatile("xor.b32 %0, %0, %1;" : "+r"(t[i]) : "r"(zero));
  float q0 = 0.f, q1 = 0.f;
#pragma unroll
  for (int i = 0; i < 16; i++) {
    const float a = bf_lo(t[i]) - m0, b = bf_hi(t[i]) - m0, c = bf_lo(t[16 + i]) - m1, d = bf_hi(t[16 + i]) - m1;
    q0 = fmaf(a, a, fmaf(b, b, q0)); q1 = fmaf(c, c, fmaf(d, d, q1));
  }
#pragma unroll
  for (int o = 16; o > 0; o >>= 1) { q0 += __shfl_xor_sync(0xffffffffu, q0, o); q1 += __shfl_xor_sync(0xffffffffu, q1, o); }
  r0 = rsqrtf(q0 * (1.0f / DM) + 1e-5f); b0 = -m0 * r0;
  r1 = rsqrtf(q1 * (1.0f / DM) + 1e-5f); b1 = -m1 * r1;
}
__device__ __forceinline__ uint32_t ln_apply(uint32_t w, float r, float b) { return pack_bf16(fmaf(bf_lo(w), r, b), fmaf(bf_hi(w), r, b)); }
__device__ __forceinline__ void ln_fixup(float (&acc)[64], uint32_t csum, float r0, float b0, float r1, float b1) {
#pragma unroll
  for (int j = 0; j < 16; j++) {
    float c0, c1;
    asm volatile("ld.shared.v2.f32 {%0, %1}, [%2];" : "=f"(c0), "=f"(c1) : "r"(csum + j * 32) : "memory");
    acc[4 * j] = fmaf(acc[4 * j], r0, b0 * c0); acc[4 * j + 1] = fmaf(acc[4 * j + 1], r0, b0 * c1);
    acc[4 * j + 2] = fmaf(acc[4 * j + 2], r1, b1 * c0); acc[4 * j + 3] = fmaf(acc[4 * j + 3], r1, b1 * c1);
  }
}

__device__ __forceinline__ unsigned long long tag_pack(float u, float v, uint32_t tag) {
  return ((unsigned long long)((__float_as_uint(u) + 128) >> 8) << 40) | ((unsigned long long)((__float_as_uint(v) + 128) >> 8) << 16) | tag;
}
__device__ __forceinline__ float4 tag_gather(const ulonglong2* src, int stride, int n, uint32_t tag) {
  float4 a = make_float4(0.f, 0.f, 0.f, 0.f);
  uint32_t spins = 0;
#pragma unroll 1
  for (int r = 0; r < n;) {
    unsigned long long u[8];
#pragma unroll
    for (int i = 0; i < 4; i++) {
      u[2 * i] = u[2 * i + 1] = tag;
      if (r + i < n) asm volatile("ld.relaxed.gpu.global.v2.u64 {%0, %1}, [%2];" : "=l"(u[2 * i]), "=l"(u[2 * i + 1]) : "l"(src + (r + i) * stride) : "memory");
    }
    bool ok = true;
#pragma unroll
    for (int i = 0; i < 8; i++) ok = ok && ((uint32_t)u[i] & 0xffffu) == tag;
    if (__all_sync(0xffffffffu, ok)) {
#pragma unroll
      for (int i = 0; i < 4; i++) {
        a.x += __uint_as_float((uint32_t)(u[2 * i] >> 32) & 0xffffff00u); a.y += __uint_as_float((uint32_t)(u[2 * i] >> 8) & 0xffffff00u);
        a.z += __uint_as_float((uint32_t)(u[2 * i + 1] >> 32) & 0xffffff00u); a.w += __uint_as_float((uint32_t)(u[2 * i + 1] >> 8) & 0xffffff00u);
      }
      r += 4;
    } else if (++spins > (1u << 22)) __trap();
  }
  return a;
}

struct Prod {
  uint32_t sbase, bars, it, rank, lane;
};
__device__ __forceinline__ uint32_t prod_acquire(Prod& p, uint32_t bytes) {
  uint32_t s = p.it & 3;
  mbar_wait_idle(p.bars + 32 + 8 * s, ((p.it >> 2) & 1) ^ 1);
  if (p.lane == 0) mbar_expect_tx(p.bars + 8 * s, bytes);
  p.it++;
  return s;
}
__device__ __forceinline__ void dep_wait(const Prod& p, uint32_t& ready, int base, int n, uint32_t target, int i) {
  if ((ready >> i) & 1) return;
  target *= launch_epoch();
  uint32_t spins = 0;
  do {
    const bool ok = (int)p.lane < n && (int)(ld_relaxed(&g_flags[base + p.lane]) - target) >= 0;
    ready = __ballot_sync(0xffffffffu, ok);
    if (++spins > (1u << 22)) __trap();
  } while (!((ready >> i) & 1));
  fence_acquire();
  __syncwarp();
  fence_async();
}
__device__ __forceinline__ void prod_gemm(Prod& p, const CUtensorMap* mA, int arow, const CUtensorMap* mB, int chunk, int k0, int k1,
                                          int base, int n, uint32_t target, int shift, uint32_t& ready) {
#pragma unroll 1
  for (int k = k0; k < k1; k++) {
    dep_wait(p, ready, base, n, target, k >> shift);
    uint32_t s = prod_acquire(p, STAGE_BYTES);
    uint32_t a = p.sbase + s * STAGE_BYTES;
    if (p.lane == 0) {
      tma_load_3d_mc(a + 16384 + p.rank * 16384, mB, p.bars + 8 * s, k * 64, chunk + p.rank * 2);
      tma_load_2d(a, mA, p.bars + 8 * s, k * 64, arow);
    }
  }
}

__global__ void __cluster_dims__(2, 1, 1) __launch_bounds__(384, 1) mega_kernel(const __grid_constant__ Params P) {
  extern __shared__ __align__(1024) uint8_t smem_raw[];
  const uint32_t sbase = smem_u32(smem_raw);
  const uint32_t bars = sbase + SM_BAR;
  const int tid = threadIdx.x, lane = tid & 31;
  const int wg = __shfl_sync(0xffffffffu, tid >> 7, 0);
  const uint32_t rank = blockIdx.x & 1;
  const int cid = blockIdx.x >> 1;
  PROFG(60); PROF(61);

  if (tid == 256) {
    for (int s = 0; s < STAGES; s++) { mbar_init(bars + 8 * s, 1); mbar_init(bars + 32 + 8 * s, 4); }
    for (int w = 0; w < 2; w++) { mbar_init(bars + 64 + 8 * w, 4); mbar_init(bars + 80 + 8 * w, 1); mbar_init(bars + 96 + 8 * w, 5); mbar_init(bars + 112 + 8 * w, 4); }
    for (int w = 0; w < 2; w++) { mbar_init(bars + 144 + 8 * w, 1); }
    mbar_init(bars + 160, 8);
    mbar_init(bars + 168, 3);
    mbar_init(bars + 176, 1);
    mbar_init(bars + 184, 1);
    asm volatile("fence.mbarrier_init.release.cluster;" ::: "memory");
  }

  __syncwarp();
  cluster_arrive_relaxed();

  if (wg == 2) {
    const int warp = __shfl_sync(0xffffffffu, tid >> 5, 0);
    if (warp == 9 && lane < M_COUNT) asm volatile("prefetch.tensormap [%0];" ::"l"(&P.maps[lane]) : "memory");
    asm volatile("setmaxnreg.dec.sync.aligned.u32 40;");
    const uint32_t task0 = opaque(P.tasks[cid][0]);
    cluster_wait();
    if (warp == 8) {
      Prod p{sbase, bars, 0, rank, (uint32_t)lane};
      {
        const uint32_t task = __shfl_sync(0xffffffffu, task0, 0);
        uint32_t ready = 0xffffffffu;
        prod_gemm(p, &P.maps[M_X], (((task >> 4) & 15) * 2 + rank) * 128, &P.maps[(task & 7) == T_QA ? M_WQ : M_WIN],
                  ((task & 7) == T_Z2 ? FH / 64 : 0) + (task >> 8) * 4, 0, STAGES, 0, 0, 0, 5, ready);
      }
      PROFT(43, 256);
#pragma unroll 1
      for (int ti = 0; ti < MAXT; ti++) {
        const uint32_t task = P.tasks[cid][ti];
        const int type = task & 7, mb = ((task >> 4) & 15) * 2 + rank, idx = task >> 8;
        if (type == T_NONE) break;
        const int arow = mb * 128;
        int mA = M_XN, mB = M_WIN, chunk = idx * 4, nk = 16, base = F_XN + mb, n = 1, shift = 5;
        uint32_t target = 8;
        int k0 = 0;
        if (type == T_Z2) chunk += FH / 64;
        else if (type == T_QA) mB = M_WQ;
        else if (type == T_G) { mA = M_WSP; mB = M_Z2; nk = 32; base = F_Z2N; n = 16; target = 14; shift = 1; }
        else if (type == T_S) { mA = M_O_LD; mB = M_WO; k0 = P.krange[cid][0]; nk = P.krange[cid][1]; base = F_O + mb * 32; n = 32; target = 2; shift = 1; }
        else if (type == T_Y) { mA = M_H_LD; mB = M_WOUT; nk = 28; base = F_H + mb * 8; n = 7; target = 2; shift = 2; }
        if (ti == 0) { mA = M_X; n = 0; k0 = STAGES; }
        uint32_t ready = n ? 0 : 0xffffffffu;
        prod_gemm(p, &P.maps[mA], arow, &P.maps[mB], chunk, k0, nk, base, n, target, shift, ready);
        if (type == T_QA) {
          const int kvrow = (idx >> 2) * SK + (SK - WIN);
#pragma unroll 1
          for (int j = 0; j < 16; j++) {
            const bool isK = j < 2 || (j < 14 && !(j & 1));
            const int ch = (j < 2 ? j : j >= 14 ? j - 12 : isK ? (j >> 1) + 1 : (j >> 1) - 1) & 3;
            uint32_t s = prod_acquire(p, 32768);
            if (lane == 0) tma_load_2d_mc(sbase + s * STAGE_BYTES + rank * 16384, &P.maps[isK ? M_K : M_V], bars + 8 * s, rank * 64, kvrow + ch * 128);
          }
        }
        if (type == T_S) {
          ready = 0;
          dep_wait(p, ready, F_SY + mb * 4 + idx, 1, 2, 0);
          const uint32_t s = prod_acquire(p, 32768);
          if (lane < 2) tma_load_2d(sbase + s * STAGE_BYTES + lane * 16384, &P.maps[M_SY_LD], bars + 8 * s, idx * 256 + 128 + lane * 64, arow);
        }
      }
    } else if (warp == 9 || warp == 10) {
      const int w = warp - 9;
      {
        const uint32_t task = P.tasks[cid][0];
        const int type = task & 7, mb = ((task >> 4) & 15) * 2 + rank, tile = type == T_Z2 ? task >> 8 : 7;
        const uint32_t slab = sbase + SM_STG + w * 16384;
        const uint32_t tag = launch_epoch() & 0xffffu;
        for (int i = 0; i <= X_DELAY; i++) mbar_wait(bars + 8 * (i & 3), (i >> 2) & 1);
        if (lane == 0) {
          const size_t off = (size_t)(blockIdx.x * 16 + w * 8) * DM;
          mbar_expect_tx(bars + 176 + 8 * w, 16384);
          asm volatile("cp.async.bulk.shared::cluster.global.mbarrier::complete_tx::bytes [%0], [%1], 16384, [%2];" ::"r"(slab), "l"(P.x + off), "r"(bars + 176 + 8 * w) : "memory");
          mbar_wait(bars + 96 + 8 * w, 0);
          fence_async_smem();
          mbar_expect_tx(bars + 176 + 8 * w, 16384);
          tma_load_3d(slab, &P.maps[type == T_QA ? M_WQ : M_WIN], bars + 176 + 8 * w, mb * 64, (type == T_Z2 ? FH / 64 : 0) + (task >> 8) * 4 + w * 2);
        }
        __syncwarp();
        mbar_wait(bars + 176 + 8 * w, 1);
        float4 a = make_float4(0.f, 0.f, 0.f, 0.f);
#pragma unroll 1
        for (int r = 0; r < 64; r += 8) {
          uint32_t v0[8], v1[8];
#pragma unroll
          for (int i = 0; i < 8; i++)
            asm volatile("ld.shared.v2.b32 {%0, %1}, [%2];" : "=r"(v0[i]), "=r"(v1[i]) : "r"(slab + (lane >> 4) * 8192 + (r + i) * 128 + ((((lane & 15) >> 1) ^ i) << 4) + (lane & 1) * 8) : "memory");
#pragma unroll
          for (int i = 0; i < 8; i += 2) {
            a.x += bf_lo(v0[i]) + bf_lo(v0[i + 1]); a.y += bf_hi(v0[i]) + bf_hi(v0[i + 1]);
            a.z += bf_lo(v1[i]) + bf_lo(v1[i + 1]); a.w += bf_hi(v1[i]) + bf_hi(v1[i + 1]);
          }
        }
        asm volatile("st.relaxed.gpu.global.v2.u64 [%0], {%1, %2};" ::"l"(&g_csum[(tile * 16 + mb) * 64 + w * 32 + lane]), "l"(tag_pack(a.x, a.y, tag)), "l"(tag_pack(a.z, a.w, tag)) : "memory");
        a = tag_gather(&g_csum[tile * 16 * 64 + w * 32 + lane], 64, 16, tag);
        asm volatile("st.shared.v4.f32 [%0], {%1, %2, %3, %4};" ::"r"(sbase + SM_CSUM + w * 512 + lane * 16), "f"(a.x), "f"(a.y), "f"(a.z), "f"(a.w) : "memory");
        __syncwarp();
        if (lane == 0) mbar_arrive(bars + 168);
        PROFT(50, 288);
        if (type == T_Z2) {
          mbar_wait_idle(bars + 112 + 8 * w, 0);
          a = tag_gather(reinterpret_cast<const ulonglong2*>(&g_stats[mb * 128 + w * 64 + lane * 2]), SEQ / 2, 7, tag);
          const float m0 = a.x * (1.0f / FH), m1 = a.z * (1.0f / FH);
          const float q0 = rsqrtf(fmaxf(fmaf(-m0, m0, a.y * (1.0f / FH)), 0.f) + 4e-5f);
          const float q1 = rsqrtf(fmaxf(fmaf(-m1, m1, a.w * (1.0f / FH)), 0.f) + 4e-5f);
          asm volatile("st.shared.v4.b32 [%0], {%1, %2, %3, %4};" ::"r"(sbase + SM_STAT + w * 512 + lane * 16), "r"(pack_bf16(q0, q0)), "r"(pack_bf16(-m0 * q0, -m0 * q0)),
                       "r"(pack_bf16(q1, q1)), "r"(pack_bf16(-m1 * q1, -m1 * q1)) : "memory");
          __syncwarp();
          if (lane == 0) mbar_arrive(bars + 144 + 8 * w);
        }
      }
      if (lane == 0) {
        uint32_t sc = 0;
#pragma unroll 1
        for (int ti = 0; ti < MAXT; ti++) {
          const uint32_t task = P.tasks[cid][ti];
          const int type = task & 7, mb = ((task >> 4) & 15) * 2 + rank, idx = task >> 8;
          if (type == T_NONE) break;
          if (type == T_S) {
            flag_wait(F_SY + mb * 4 + idx, 2);
            fence_async();
            mbar_expect_tx(bars + 176 + 8 * w, 16384);
            tma_load_2d(sbase + SM_STG + w * 16384, &P.maps[M_SY_ST], bars + 176 + 8 * w, idx * 256, mb * 128 + w * 64);
            tma_load_2d(sbase + SM_STG + w * 16384 + 8192, &P.maps[M_SY_ST], bars + 176 + 8 * w, idx * 256 + 64, mb * 128 + w * 64);
            const bf16* po = P.out + (size_t)(mb * 128 + w * 64) * DM + idx * 256;
#pragma unroll 1
            for (int q = 0; q < 64; q++, po += DM)
              asm volatile("prefetch.global.L2 [%0];\nprefetch.global.L2 [%0 + 128];\nprefetch.global.L2 [%0 + 256];\nprefetch.global.L2 [%0 + 384];" ::"l"(po));
          }
          if (type == T_Z1 || type == T_S) continue;
          const int mi = type == T_Z2 ? M_Z2_ST : type == T_QA ? M_O_ST : type == T_G ? M_H_ST : M_SY_ST;
          const int f = type == T_Z2 ? F_Z2N + mb : type == T_QA ? F_O + mb * 32 + idx * 2 : type == T_G ? F_H + mb * 8 + idx : F_SY + mb * 4 + idx;
#pragma unroll 1
          for (int q = 0; q < 2; q++, sc++) {
            mbar_wait_idle(bars + 64 + w * 8, sc & 1);
            tma_store_2d(&P.maps[mi], sbase + SM_STG + w * 16384, idx * 256 + q * 128, mb * 128 + w * 64);
            tma_store_2d(&P.maps[mi], sbase + SM_STG + w * 16384 + 8192, idx * 256 + q * 128 + 64, mb * 128 + w * 64);
            asm volatile("cp.async.bulk.commit_group;" ::: "memory");
            asm volatile("cp.async.bulk.wait_group.read 0;" ::: "memory");
            mbar_arrive(bars + 80 + w * 8);
            if (q == 1 || type == T_QA) {
              asm volatile("cp.async.bulk.wait_group 0;" ::: "memory");
              red_release(&g_flags[f + (type == T_QA ? q : 0)]);
            }
          }
        }
      }
    } else {
      const uint32_t task = P.tasks[cid][0];
      {
        const int mb = ((task >> 4) & 15) * 2 + rank;
        {
          mbar_wait(bars + 24, 0);
          const size_t off = ((size_t)(blockIdx.x >> 5) * SK + (SK - WIN) + (blockIdx.x & 31) * 16) * 128 + lane * 64;
          asm volatile("prefetch.global.L2 [%0];" ::"l"(P.kv[0] + off));
          asm volatile("prefetch.global.L2 [%0];" ::"l"(P.kv[1] + off));
        }
        if (lane == 0) {
          mbar_wait(bars + 176, 0);
          mbar_wait(bars + 184, 0);
          asm volatile("cp.async.bulk.global.shared::cta.bulk_group [%0], [%1], 32768;" ::"l"(P.out + (size_t)blockIdx.x * 16 * DM), "r"(sbase + SM_STG) : "memory");
          asm volatile("cp.async.bulk.commit_group;" ::: "memory");
          asm volatile("cp.async.bulk.wait_group.read 0;" ::: "memory");
          mbar_arrive(bars + 96);
          mbar_arrive(bars + 104);
          asm volatile("cp.async.bulk.wait_group 0;" ::: "memory");
        }
        __syncwarp();
        mbar_wait(bars + 160, 0);
        if (lane == 0) red_release(&g_flags[F_XN + (blockIdx.x >> 3)]);
        __syncwarp();
        if (lane == 0) asm volatile("st.shared.u32 [%0], %1;" ::"r"(bars + 128), "r"(launch_epoch()) : "memory");
        flag_wait(F_XN + mb, 8);
        const float4 u0 = __ldcg(reinterpret_cast<const float4*>(&g_xstat[mb * 128]) + lane);
        const float4 u1 = __ldcg(reinterpret_cast<const float4*>(&g_xstat[mb * 128 + 64]) + lane);
        asm volatile("st.shared.v4.f32 [%0], {%1, %2, %3, %4};" ::"r"(sbase + SM_STAT + lane * 16), "f"(u0.x), "f"(u0.y), "f"(u0.z), "f"(u0.w) : "memory");
        asm volatile("st.shared.v4.f32 [%0], {%1, %2, %3, %4};" ::"r"(sbase + SM_STAT + 512 + lane * 16), "f"(u1.x), "f"(u1.y), "f"(u1.z), "f"(u1.w) : "memory");
        __syncwarp();
        if (lane == 0) mbar_arrive(bars + 168);
        PROFT(42, 352);
      }
    }
  } else {
    asm volatile("setmaxnreg.inc.sync.aligned.u32 232;");
    const int warp = tid >> 5;
    uint32_t t[64];
#pragma unroll
    for (int i = 0; i < 64; i++) t[i] = 0;
    cluster_wait();
    PROF(62);

    Ctx c;
    c.sbase = sbase; c.bars = bars; c.it = 0; c.sc = 0; c.wg = wg; c.t = tid & 127; c.one = P.one;
    c.d16 = (sbase & ~0x3FFFFu) >> 4;
    asm volatile("mapa.shared::cluster.u32 %0, %1, %2;" : "=r"(c.rel) : "r"(bars + 32), "r"(tid & 1));
    c.stg = sbase + SM_STG + wg * 16384;
    {
      const int row = (warp & 3) * 16 + ((lane >> 3) & 1) * 8 + (lane & 7);
      c.st_off = row * 128;
      c.st_sw = (lane >> 4) ^ (lane & 7);
    }
    if (wg == 1) bar_arrive(1, 256);
    float accA[64], accB[64];
    int pend = 2, ptype = T_NONE;
    float s0 = 0.f, s1 = 0.f, q0 = 0.f, q1 = 0.f;
    wait_full(c, 0);
    PROF(40);
    mma_step<true>(c, accA, accB, 0);
#pragma unroll 1
    for (int ti = 0;; ti++) {
      const uint32_t task = P.tasks[cid][ti];
      const int type = task & 7, mb = ((task >> 4) & 15) * 2 + rank;
      const bool is_qa = type == T_QA;
      PROF(ti * 4);
      uint32_t it = c.it + 1;
      const uint32_t nk = type == T_G ? 32 : type == T_Y ? 28 : (type == T_S) ? P.krange[cid][1] - P.krange[cid][0] : 16;
      const uint32_t last = c.it + nk - 1;
      const uint32_t period = type == T_G ? 4 : ti == 0 ? LN_PERIOD : (ptype == T_Y && nk >= 22) ? 3 : 2;
      const bool raw = ti == 0;
      uint32_t slot = it + (wg ? period >> 1 : 0) + (raw ? LN_DELAY : 0);
#pragma unroll 1
      for (; it < last; it++) {
        wait_full(c, it);
        mma_step<false>(c, accA, accB, it);
        wgmma_wait<1>();
        release(c, it - 1);
        if (it == slot) {
          const uint32_t stat = sbase + SM_STAT + (wg * 64 + (warp & 3) * 16 + (lane >> 2)) * 8;
          slot += period;
          if (pend > 2) {
            if (ptype == T_Y) {
#pragma unroll
              for (int i = 0; i < 16; i++) t[i] = pack_bf16(silu(bf_lo(t[i])), silu(bf_hi(t[i])));
            } else {
#pragma unroll
              for (int i = 0; i < 16; i++) {
                const float a = gelu2_tanh(bf_lo(t[i])), b = gelu2_tanh(bf_hi(t[i]));
                t[i] = pack_bf16(a, b);
                if (i & 1) { s1 += a + b; q1 = fmaf(a, a, fmaf(b, b, q1)); }
                else { s0 += a + b; q0 = fmaf(a, a, fmaf(b, b, q0)); }
              }
            }
            rotate16(t);
            if (pend == 3) {
              if (ptype == T_Z1) pend = 1;
              else if (ptype == T_Z2) {
                slot += period;
#pragma unroll
                for (int o = 1; o < 4; o <<= 1) {
                  s0 += __shfl_xor_sync(0xffffffffu, s0, o); q0 += __shfl_xor_sync(0xffffffffu, q0, o);
                  s1 += __shfl_xor_sync(0xffffffffu, s1, o); q1 += __shfl_xor_sync(0xffffffffu, q1, o);
                }
                if ((lane & 3) < 2) {
                  const uint32_t t0 = P.tasks[cid][0];
                  const int row = (((t0 >> 4) & 15) * 2 + rank) * 128 + wg * 64 + (warp & 3) * 16 + (lane >> 2) + (lane & 1) * 8;
                  uint32_t epoch;
                  asm volatile("ld.shared.u32 %0, [%1];" : "=r"(epoch) : "r"(bars + 128) : "memory");
                  asm volatile("st.relaxed.gpu.global.u64 [%0], %1;" ::"l"(&g_stats[(t0 >> 8) * SEQ + row]),
                               "l"(tag_pack((lane & 1) ? s1 : s0, (lane & 1) ? q1 : q0, epoch & 0xffffu)) : "memory");
                }
                __syncwarp();
                if (lane == 0) mbar_arrive(bars + 112 + 8 * wg);
              }
            }
          } else if (ptype == T_NONE) {
            if (pend == 2) {
              mbar_wait(bars + 176 + 8 * wg, 0);
#pragma unroll
              for (int i = 0; i < 8; i++)
                asm volatile("ld.shared.v4.u32 {%0, %1, %2, %3}, [%4];" : "=r"(t[4 * i]), "=r"(t[4 * i + 1]), "=r"(t[4 * i + 2]), "=r"(t[4 * i + 3]) : "r"(c.stg + (warp & 3) * 4096 + i * 512 + lane * 16) : "memory");
              __syncwarp();
              if (lane == 0) mbar_arrive(bars + 96 + 8 * wg);
              ln_stats(t, s0, q0, s1, q1, t[32]);
            }
            if (pend == 1) {
              const int row = blockIdx.x * 16 + warp * 2;
              uint4* xo = reinterpret_cast<uint4*>(g_xn + (size_t)row * DM);
#pragma unroll
              for (int i = 0; i < 8; i++) {
                const float r = i < 4 ? s0 : s1, b = i < 4 ? q0 : q1;
                xo[i * 32 + lane] = make_uint4(ln_apply(t[4 * i], r, b), ln_apply(t[4 * i + 1], r, b), ln_apply(t[4 * i + 2], r, b), ln_apply(t[4 * i + 3], r, b));
              }
              if (lane == 0) *reinterpret_cast<float4*>(&g_xstat[row]) = make_float4(s0, q0, s1, q1);
              __syncwarp();
              if (lane == 0) mbar_arrive(bars + 160);
              PROF(41);
            }
          } else {
            if (ptype == T_Z2) {
              uint32_t a0, b0, a1, b1;
              mbar_wait(bars + 144 + 8 * wg, 0);
              asm volatile("ld.shared.v2.b32 {%0, %1}, [%2];" : "=r"(a0), "=r"(b0) : "r"(stat) : "memory");
              asm volatile("ld.shared.v2.b32 {%0, %1}, [%2];" : "=r"(a1), "=r"(b1) : "r"(stat + 64) : "memory");
#pragma unroll
              for (int i = 0; i < 32; i++) t[i] = fma_bf2(t[i], (i & 1) ? a1 : a0, (i & 1) ? b1 : b0);
            }
            half_store(c, t);
          }
          if (--pend == 0) slot = last;
        }
      }
      uint32_t b0 = 0, b1 = 0;
      if (type == T_G) {
        const bf16* bp = P.b_sp + mb * 128 + wg * 64 + (warp & 3) * 16 + (lane >> 2);
        asm volatile("ld.global.nc.u16 %0, [%1];" : "=r"(b0) : "l"(bp));
        asm volatile("ld.global.nc.u16 %0, [%1];" : "=r"(b1) : "l"(bp + 8));
      }
      wait_full(c, it);
      if (is_qa) stg_acquire(c);
      bar_sync(1 + wg, 256);
      mma_step<false>(c, accA, accB, it);
      bar_arrive(2 - wg, 256);
      wgmma_wait<1>();
      release(c, it - 1);
      wgmma_wait<0>();
      release(c, it);
      it++;
      PROF(ti * 4 + 1);
      if (type == T_S) {
        const int col = (task >> 8) * 256, row = mb * 128 + wg * 64;
        PROF(44);
        mbar_wait(bars + 176 + 8 * wg, 0);
        PROF(45);
#pragma unroll 1
        for (int h = 0;; h++) {
          final_half(c, accA, h ? stage_addr(c, it) + wg * 8192 : c.stg, h ? 16384 : 8192, &P.maps[M_OUT], col + h * 128, row);
          if (h) break;
          PROF(46);
#pragma unroll
          for (int i = 0; i < 64; i++) accA[i] = accB[i];
          wait_full(c, it);
          PROF(47);
        }
        PROF(48);
        if (c.t == 0) asm volatile("cp.async.bulk.wait_group.read 0;" ::: "memory");
        PROF(ti * 4 + 2);
        break;
      }
      if (raw) {
        const uint32_t stat = sbase + SM_STAT + (wg * 64 + (warp & 3) * 16 + (lane >> 2)) * 8;
        mbar_wait(bars + 168, 0);
        asm volatile("ld.shared.v2.f32 {%0, %1}, [%2];" : "=f"(s0), "=f"(q0) : "r"(stat) : "memory");
        asm volatile("ld.shared.v2.f32 {%0, %1}, [%2];" : "=f"(s1), "=f"(q1) : "r"(stat + 64) : "memory");
        ln_fixup(accA, sbase + SM_CSUM + (lane & 3) * 8, s0, q0, s1, q1);
        ln_fixup(accB, sbase + SM_CSUM + 512 + (lane & 3) * 8, s0, q0, s1, q1);
      }
      if (is_qa) {
        acc_write(c, opaque(c.stg), accA);
        Att a;
        a.qb = stage_addr(c, it + wg) + 32768;
        a.pb = stage_addr(c, it + 2 + wg) + 32768;
        float sa[64], sb[64], o[64];
#pragma unroll
        for (int i = 0; i < 64; i++) { sa[i] = 0.f; sb[i] = 0.f; }
        wait_full(c, it);
        wait_full(c, it + 1);
        fence_async_smem();
        bar_sync(1 + wg, 256);
        issue_qk<0, 8>(c, sa, c.stg, it);
        acc_write(c, a.qb, accB);
        issue_qk<0, 8>(c, sb, c.stg, it + 1);
        bar_arrive(2 - wg, 256);
        wgmma_wait<1>();
        release(c, it);
        a.it = it; a.l0 = 0.f; a.l1 = 0.f; a.r0 = 0.f; a.r1 = 0.f; a.rescale = false;
        {
          float x0, x1;
          int m[4] = {0, 0, 0, 0};
#pragma unroll
          for (int i = 0; i < 64; i += 2) m[(i >> 1) & 3] = __vimax3_s32(m[(i >> 1) & 3], __float_as_int(sa[i]), __float_as_int(sa[i + 1]));
          row_max(sa, max(m[0], m[2]), max(m[1], m[3]), x0, x1);
          a.n0 = -x0 * SM_SCALE; a.n1 = -x1 * SM_SCALE;
        }
        att_step<0, false>(c, a, 0, sa, sb, o);
#pragma unroll
        for (int i = 0; i < 64; i++) o[i] = 0.f;
#pragma unroll 1
        for (int j = 1; j < 7; j += 2) {
          att_step<1, true>(c, a, j, sb, sa, o);
          att_step<1, false>(c, a, j + 1, sa, sb, o);
        }
        att_step<2, true>(c, a, 7, sb, sa, o);
        it = a.it + 1;
        wait_full(c, it);
        fence_async_smem();
        bar_sync(1 + wg, 256);
        issue_pv<0, 8>(c, o, a.pb, it, 1);
        it++;
#pragma unroll
        for (int i = 0; i < 64; i++) { accA[i] = 0.f; accB[i] = 0.f; }
        wait_full(c, it);
        mma_step<true>(c, accA, accB, it);
        bar_arrive(2 - wg, 256);
        const float r0 = quad_rcp_sum(a.l0), r1 = quad_rcp_sum(a.l1);
        wgmma_wait<1>();
        release(c, it - 1);
        capture_scaled<0>(t, o, r0, r1);
#pragma unroll
        for (int i = 32; i < 64; i++) t[i] = 0;
      } else {
        const float r0 = 0.5f * bf_lo(b0), r1 = 0.5f * bf_lo(b1);
        if (type == T_G) {
          capture_gate<0>(t, accA, r0, r1);
          capture_gate<32>(t, accB, r0, r1);
        } else {
          capture_plain<0>(t, accA);
          capture_plain<32>(t, accB);
        }
        wait_full(c, it);
        mma_step<true>(c, accA, accB, it);
      }
      c.it = it;
      s0 = 0.f; s1 = 0.f; q0 = 0.f; q1 = 0.f;
      pend = is_qa ? 1 : (type == T_Z2 || type == T_Z1 || type == T_Y) ? 6 : 2;
      ptype = type;
      PROF(ti * 4 + 2);
      PROF(ti * 4 + 3);
    }
    wgmma_wait<0>();
    PROF(59);
  }
  __syncwarp();
  cluster_arrive_relaxed();
  cluster_wait();
  if (tid == 0) g_flags[F_EPOCH + blockIdx.x] += 1;
  PROFG(63);
}

typedef CUresult (*PFN_encodeTiled)(CUtensorMap*, CUtensorMapDataType, cuuint32_t, void*, const cuuint64_t*, const cuuint64_t*, const cuuint32_t*,
                                    const cuuint32_t*, CUtensorMapInterleave, CUtensorMapSwizzle, CUtensorMapL2promotion, CUtensorMapFloatOOBfill);

static void map_2d(PFN_encodeTiled enc, CUtensorMap* m, const void* ptr, uint64_t rows, uint64_t cols, uint32_t box_rows = 128) {
  cuuint64_t dims[2] = {cols, rows}; cuuint64_t strides[1] = {cols * 2};
  cuuint32_t box[2] = {64, box_rows}; cuuint32_t es[2] = {1, 1};
  enc(m, CU_TENSOR_MAP_DATA_TYPE_BFLOAT16, 2, const_cast<void*>(ptr), dims, strides, box, es, CU_TENSOR_MAP_INTERLEAVE_NONE,
      CU_TENSOR_MAP_SWIZZLE_128B, CU_TENSOR_MAP_L2_PROMOTION_L2_256B, CU_TENSOR_MAP_FLOAT_OOB_FILL_NONE);
}
static void map_3d(PFN_encodeTiled enc, CUtensorMap* m, const void* ptr, uint64_t rows, uint64_t cols) {
  cuuint64_t dims[3] = {64, rows, cols / 64}; cuuint64_t strides[2] = {cols * 2, 128};
  cuuint32_t box[3] = {64, 64, 2}; cuuint32_t es[3] = {1, 1, 1};
  enc(m, CU_TENSOR_MAP_DATA_TYPE_BFLOAT16, 3, const_cast<void*>(ptr), dims, strides, box, es, CU_TENSOR_MAP_INTERLEAVE_NONE,
      CU_TENSOR_MAP_SWIZZLE_128B, CU_TENSOR_MAP_L2_PROMOTION_L2_256B, CU_TENSOR_MAP_FLOAT_OOB_FILL_NONE);
}
static unsigned short mk(int type, int mp, int idx) { return (unsigned short)(type | (mp << 4) | (idx << 8)); }

#define SPLIT0 "37"
#define SPLIT1 "40"
#define SPLIT3 "37"
static void build_schedule(Params& P) {
  for (int c = 0; c < NCLUSTERS; c++) {
    for (int t = 0; t < MAXT + 2; t++) P.tasks[c][t] = 0;
    P.krange[c][0] = P.krange[c][1] = 0;
  }
  static const char* const plan[8] = {
      "q0 h1 q9 y0 s0:" SPLIT0 "-64",
      "z0 q1 h2 q12 s0:0-" SPLIT0,
      "z2 q3 q7 q10 y1 s1:" SPLIT1 "-64",
      "z1 q2 h3 q13 s1:0-" SPLIT1,
      "z4 q5 q8 q11 y2 s2:" SPLIT1 "-64",
      "z3 q4 h4 q14 s2:0-" SPLIT1,
      "z6 h0 h6 y3 s3:" SPLIT3 "-64",
      "z5 q6 h5 q15 s3:0-" SPLIT3,
  };
  for (int mp = 0; mp < 8; mp++) {
    for (int j = 0; j < 8; j++) {
      const int cl = mp * 8 + ((j + mp) & 7);
      unsigned short* T = P.tasks[cl];
      int n = 0;
      for (const char* q = plan[j]; *q;) {
        const char kind = *q++;
        int v[3] = {0, 0, 0};
        for (int f = 0; *q && *q != ' '; q++) {
          if (*q == ':' || *q == '-') f++;
          else v[f] = v[f] * 10 + (*q - '0');
        }
        while (*q == ' ') q++;
        if (kind == 'z') T[n++] = mk(T_Z2, mp, v[0]);
        else if (kind == 'q') T[n++] = mk(T_QA, mp, v[0]);
        else if (kind == 'h') { T[n++] = mk(T_Z1, mp, v[0]); T[n++] = mk(T_G, mp, v[0]); }
        else if (kind == 'y') T[n++] = mk(T_Y, mp, v[0]);
        else { T[n++] = mk(T_S, mp, v[0]); P.krange[cl][0] = (unsigned char)v[1]; P.krange[cl][1] = (unsigned char)v[2]; }
      }
    }
  }
}

extern "C" void kernel_launch(void* const* d_in, const int* in_sizes, int n_in, void* d_out, int out_size) {
  (void)in_sizes; (void)n_in; (void)out_size;
  static PFN_encodeTiled enc = nullptr;
  static void *p_xn, *p_z2, *p_o, *p_h, *p_sy;
  if (!enc) {
    void* fn = nullptr; cudaDriverEntryPointQueryResult qr;
    cudaGetDriverEntryPoint("cuTensorMapEncodeTiled", &fn, cudaEnableDefault, &qr);
    enc = (PFN_encodeTiled)fn;
    cudaGetSymbolAddress(&p_xn, g_xn); cudaGetSymbolAddress(&p_z2, g_z2); cudaGetSymbolAddress(&p_o, g_o);
    cudaGetSymbolAddress(&p_h, g_h); cudaGetSymbolAddress(&p_sy, g_sy);
    cudaFuncSetAttribute(mega_kernel, cudaFuncAttributeMaxDynamicSharedMemorySize, SMEM_BYTES);
  }
  Params P;
  map_2d(enc, &P.maps[M_XN], p_xn, SEQ, DM);
  map_2d(enc, &P.maps[M_WSP], d_in[7], SEQ, SEQ);
  map_2d(enc, &P.maps[M_O_LD], p_o, SEQ, HD);
  map_2d(enc, &P.maps[M_H_LD], p_h, SEQ, FH);
  map_2d(enc, &P.maps[M_X], d_in[0], SEQ, DM);
  map_2d(enc, &P.maps[M_SY_LD], p_sy, SEQ, DM);
  map_2d(enc, &P.maps[M_K], d_in[1], 4 * SK, 128);
  map_2d(enc, &P.maps[M_V], d_in[2], 4 * SK, 128);
  map_3d(enc, &P.maps[M_WIN], d_in[6], DM, FF);
  map_3d(enc, &P.maps[M_WQ], d_in[3], DM, HD);
  map_3d(enc, &P.maps[M_Z2], p_z2, SEQ, FH);
  map_3d(enc, &P.maps[M_WO], d_in[4], HD, DM);
  map_3d(enc, &P.maps[M_WOUT], d_in[9], FH, DM);
  map_2d(enc, &P.maps[M_Z2_ST], p_z2, SEQ, FH, 64);
  map_2d(enc, &P.maps[M_O_ST], p_o, SEQ, HD, 64);
  map_2d(enc, &P.maps[M_H_ST], p_h, SEQ, FH, 64);
  map_2d(enc, &P.maps[M_SY_ST], p_sy, SEQ, DM, 64);
  map_2d(enc, &P.maps[M_OUT], d_out, SEQ, DM, 64);
  P.x = (const bf16*)d_in[0];
  P.out = (bf16*)d_out;
  P.b_sp = (const bf16*)d_in[8];
  P.kv[0] = (const bf16*)d_in[1];
  P.kv[1] = (const bf16*)d_in[2];
  P.one = 1;
  build_schedule(P);
  mega_kernel<<<NCLUSTERS * 2, 384, SMEM_BYTES, cudaStreamPerThread>>>(P);
}
```

```cpp
#include <cuda_runtime.h>
#include <cuda_bf16.h>
#include <cuda.h>
#include <stdint.h>

typedef __nv_bfloat16 bf16;

constexpr int SEQ = 2048, DM = 1024, HD = 4096, FF = 3584, FH = 1792, SK = 2048, WIN = 512;
constexpr int NCLUSTERS = 64;
constexpr int MAXT = 8;
#define LN_DELAY 2

__device__ bf16 g_xn[SEQ * DM];
__device__ bf16 g_z2[SEQ * FH];
__device__ bf16 g_o[SEQ * HD];
__device__ bf16 g_h[SEQ * FH];
__device__ bf16 g_sy[SEQ * DM];
constexpr int F_XN = 0;
constexpr int F_Z2N = 16;
constexpr int F_O = 64;
constexpr int F_H = 576;
constexpr int F_SY = 704;
constexpr int F_EPOCH = 768;
constexpr int F_COUNT = 1024;
__device__ __align__(16) unsigned int g_flags[F_COUNT];
__device__ float2 g_xstat[SEQ];
__device__ ulonglong2 g_csum[8 * 16 * 64];
__device__ __align__(16) unsigned long long g_stats[8 * SEQ];

enum { M_XN = 0, M_WSP, M_O_LD, M_H_LD, M_X, M_SY_LD, M_K, M_V,
       M_WIN, M_WQ, M_Z2, M_WO, M_WOUT,
       M_Z2_ST, M_O_ST, M_H_ST, M_SY_ST, M_OUT,
       M_COUNT };
enum { T_NONE = 0, T_Z2, T_QA, T_Z1, T_G, T_Y, T_S };

struct Params {
  CUtensorMap maps[M_COUNT];
  const bf16* x;
  bf16* out;
  const bf16* b_sp;
  const bf16* kv[2];
  int one;
  unsigned char tasks[8][MAXT];
  unsigned char krange[8][2];
};

constexpr int STAGES = 4;
constexpr int STAGE_BYTES = 49152;
constexpr int SM_STG = STAGES * STAGE_BYTES;
constexpr int SM_BAR = SM_STG + 32768;
constexpr int SM_STAT = SM_BAR + 256;
constexpr int SM_CSUM = SM_STAT + 1024;
constexpr int SMEM_BYTES = SM_CSUM + 1024;

template <int TB>
__device__ __forceinline__ void wgmma_ss_n128(float (&d)[64], uint64_t da, uint64_t db, int scale_d) {
  asm volatile("{\n.reg .pred p;\nsetp.ne.b32 p, %66, 0;\n"
    "wgmma.mma_async.sync.aligned.m64n128k16.f32.bf16.bf16 {%0, %1, %2, %3, %4, %5, %6, %7, %8, %9, %10, %11, %12, %13, %14, %15, %16, %17, %18, %19, %20, %21, %22, %23, %24, %25, %26, %27, %28, %29, %30, %31, %32, %33, %34, %35, %36, %37, %38, %39, %40, %41, %42, %43, %44, %45, %46, %47, %48, %49, %50, %51, %52, %53, %54, %55, %56, %57, %58, %59, %60, %61, %62, %63}, %64, %65, p, 1, 1, 0, %67;\n}\n"
    : "+f"(d[0]), "+f"(d[1]), "+f"(d[2]), "+f"(d[3]), "+f"(d[4]), "+f"(d[5]), "+f"(d[6]), "+f"(d[7]), "+f"(d[8]), "+f"(d[9]), "+f"(d[10]), "+f"(d[11]), "+f"(d[12]), "+f"(d[13]), "+f"(d[14]), "+f"(d[15]), "+f"(d[16]), "+f"(d[17]), "+f"(d[18]), "+f"(d[19]), "+f"(d[20]), "+f"(d[21]), "+f"(d[22]), "+f"(d[23]), "+f"(d[24]), "+f"(d[25]), "+f"(d[26]), "+f"(d[27]), "+f"(d[28]), "+f"(d[29]), "+f"(d[30]), "+f"(d[31]), "+f"(d[32]), "+f"(d[33]), "+f"(d[34]), "+f"(d[35]), "+f"(d[36]), "+f"(d[37]), "+f"(d[38]), "+f"(d[39]), "+f"(d[40]), "+f"(d[41]), "+f"(d[42]), "+f"(d[43]), "+f"(d[44]), "+f"(d[45]), "+f"(d[46]), "+f"(d[47]), "+f"(d[48]), "+f"(d[49]), "+f"(d[50]), "+f"(d[51]), "+f"(d[52]), "+f"(d[53]), "+f"(d[54]), "+f"(d[55]), "+f"(d[56]), "+f"(d[57]), "+f"(d[58]), "+f"(d[59]), "+f"(d[60]), "+f"(d[61]), "+f"(d[62]), "+f"(d[63])
    : "l"(da), "l"(db), "r"(scale_d), "n"(TB));
}
__device__ __forceinline__ void wgmma_ss_n256(float (&d)[64], float (&e)[64], uint64_t da, uint64_t db, int scale_d) {
  asm volatile("{\n.reg .pred p;\nsetp.ne.b32 p, %130, 0;\n"
    "wgmma.mma_async.sync.aligned.m64n256k16.f32.bf16.bf16 {%0, %1, %2, %3, %4, %5, %6, %7, %8, %9, %10, %11, %12, %13, %14, %15, %16, %17, %18, %19, %20, %21, %22, %23, %24, %25, %26, %27, %28, %29, %30, %31, %32, %33, %34, %35, %36, %37, %38, %39, %40, %41, %42, %43, %44, %45, %46, %47, %48, %49, %50, %51, %52, %53, %54, %55, %56, %57, %58, %59, %60, %61, %62, %63, %64, %65, %66, %67, %68, %69, %70, %71, %72, %73, %74, %75, %76, %77, %78, %79, %80, %81, %82, %83, %84, %85, %86, %87, %88, %89, %90, %91, %92, %93, %94, %95, %96, %97, %98, %99, %100, %101, %102, %103, %104, %105, %106, %107, %108, %109, %110, %111, %112, %113, %114, %115, %116, %117, %118, %119, %120, %121, %122, %123, %124, %125, %126, %127}, %128, %129, p, 1, 1, 0, 1;\n}\n"
    : "+f"(d[0]), "+f"(d[1]), "+f"(d[2]), "+f"(d[3]), "+f"(d[4]), "+f"(d[5]), "+f"(d[6]), "+f"(d[7]), "+f"(d[8]), "+f"(d[9]), "+f"(d[10]), "+f"(d[11]), "+f"(d[12]), "+f"(d[13]), "+f"(d[14]), "+f"(d[15]), "+f"(d[16]), "+f"(d[17]), "+f"(d[18]), "+f"(d[19]), "+f"(d[20]), "+f"(d[21]), "+f"(d[22]), "+f"(d[23]), "+f"(d[24]), "+f"(d[25]), "+f"(d[26]), "+f"(d[27]), "+f"(d[28]), "+f"(d[29]), "+f"(d[30]), "+f"(d[31]), "+f"(d[32]), "+f"(d[33]), "+f"(d[34]), "+f"(d[35]), "+f"(d[36]), "+f"(d[37]), "+f"(d[38]), "+f"(d[39]), "+f"(d[40]), "+f"(d[41]), "+f"(d[42]), "+f"(d[43]), "+f"(d[44]), "+f"(d[45]), "+f"(d[46]), "+f"(d[47]), "+f"(d[48]), "+f"(d[49]), "+f"(d[50]), "+f"(d[51]), "+f"(d[52]), "+f"(d[53]), "+f"(d[54]), "+f"(d[55]), "+f"(d[56]), "+f"(d[57]), "+f"(d[58]), "+f"(d[59]), "+f"(d[60]), "+f"(d[61]), "+f"(d[62]), "+f"(d[63]), "+f"(e[0]), "+f"(e[1]), "+f"(e[2]), "+f"(e[3]), "+f"(e[4]), "+f"(e[5]), "+f"(e[6]), "+f"(e[7]), "+f"(e[8]), "+f"(e[9]), "+f"(e[10]), "+f"(e[11]), "+f"(e[12]), "+f"(e[13]), "+f"(e[14]), "+f"(e[15]), "+f"(e[16]), "+f"(e[17]), "+f"(e[18]), "+f"(e[19]), "+f"(e[20]), "+f"(e[21]), "+f"(e[22]), "+f"(e[23]), "+f"(e[24]), "+f"(e[25]), "+f"(e[26]), "+f"(e[27]), "+f"(e[28]), "+f"(e[29]), "+f"(e[30]), "+f"(e[31]), "+f"(e[32]), "+f"(e[33]), "+f"(e[34]), "+f"(e[35]), "+f"(e[36]), "+f"(e[37]), "+f"(e[38]), "+f"(e[39]), "+f"(e[40]), "+f"(e[41]), "+f"(e[42]), "+f"(e[43]), "+f"(e[44]), "+f"(e[45]), "+f"(e[46]), "+f"(e[47]), "+f"(e[48]), "+f"(e[49]), "+f"(e[50]), "+f"(e[51]), "+f"(e[52]), "+f"(e[53]), "+f"(e[54]), "+f"(e[55]), "+f"(e[56]), "+f"(e[57]), "+f"(e[58]), "+f"(e[59]), "+f"(e[60]), "+f"(e[61]), "+f"(e[62]), "+f"(e[63])
    : "l"(da), "l"(db), "r"(scale_d));
}

__device__ __forceinline__ uint32_t smem_u32(const void* p) { return (uint32_t)__cvta_generic_to_shared(p); }
__device__ __forceinline__ void mbar_init(uint32_t bar, uint32_t cnt) { asm volatile("mbarrier.init.shared::cta.b64 [%0], %1;" ::"r"(bar), "r"(cnt) : "memory"); }
__device__ __forceinline__ void mbar_expect_tx(uint32_t bar, uint32_t bytes) { asm volatile("mbarrier.arrive.expect_tx.shared::cta.b64 _, [%0], %1;" ::"r"(bar), "r"(bytes) : "memory"); }
__device__ __forceinline__ void mbar_arrive(uint32_t bar) { asm volatile("mbarrier.arrive.shared::cta.b64 _, [%0];" ::"r"(bar) : "memory"); }
__device__ __forceinline__ void mbar_wait(uint32_t bar, uint32_t parity) {
  asm volatile(
      "{\n.reg .pred p;\n.reg .u32 n;\nmov.u32 n, 0;\n"
      "LAB_WAIT:\nmbarrier.try_wait.parity.shared::cta.b64 p, [%0], %1;\n@p bra LAB_DONE;\n"
      "add.u32 n, n, 1;\nsetp.lt.u32 p, n, 4194304;\n@p bra LAB_WAIT;\ntrap;\nLAB_DONE:\n}\n" ::"r"(bar), "r"(parity) : "memory");
}
__device__ __forceinline__ void mbar_wait_idle(uint32_t bar, uint32_t parity) {
  asm volatile(
      "{\n.reg .pred p;\n.reg .u32 n;\nmov.u32 n, 0;\n"
      "LAB_WAIT:\nmbarrier.try_wait.parity.shared::cta.b64 p, [%0], %1, 1000;\n@p bra LAB_DONE;\n"
      "add.u32 n, n, 1;\nsetp.lt.u32 p, n, 4194304;\n@p bra LAB_WAIT;\ntrap;\nLAB_DONE:\n}\n" ::"r"(bar), "r"(parity) : "memory");
}
__device__ __forceinline__ bool mbar_test2(uint32_t bar0, uint32_t par0, uint32_t bar1, uint32_t par1) {
  uint32_t ok;
  asm volatile("{\n.reg .pred p, q;\nmbarrier.test_wait.parity.shared::cta.b64 p, [%1], %2;\nmbarrier.test_wait.parity.shared::cta.b64 q, [%3], %4;\n"
               "and.pred p, p, q;\nvote.sync.all.pred p, p, 0xffffffff;\nselp.u32 %0, 1, 0, p;\n}\n" : "=r"(ok) : "r"(bar0), "r"(par0), "r"(bar1), "r"(par1) : "memory");
  return ok != 0;
}
__device__ __forceinline__ void tma_load_2d(uint32_t dst, const CUtensorMap* tm, uint32_t bar, int c0, int c1) {
  asm volatile("cp.async.bulk.tensor.2d.shared::cluster.global.mbarrier::complete_tx::bytes [%0], [%1, {%3, %4}], [%2];" ::"r"(dst), "l"(tm), "r"(bar), "r"(c0), "r"(c1) : "memory");
}
__device__ __forceinline__ void tma_load_2d_mc(uint32_t dst, const CUtensorMap* tm, uint32_t bar, int c0, int c1) {
  asm volatile("cp.async.bulk.tensor.2d.shared::cluster.global.mbarrier::complete_tx::bytes.multicast::cluster [%0], [%1, {%3, %4}], [%2], %5;" ::"r"(dst), "l"(tm), "r"(bar), "r"(c0), "r"(c1), "h"((uint16_t)3) : "memory");
}
__device__ __forceinline__ void tma_load_3d_mc(uint32_t dst, const CUtensorMap* tm, uint32_t bar, int row, int chunk) {
  asm volatile("cp.async.bulk.tensor.3d.shared::cluster.global.mbarrier::complete_tx::bytes.multicast::cluster [%0], [%1, {%3, %4, %5}], [%2], %6;" ::"r"(dst), "l"(tm), "r"(bar), "r"(0), "r"(row), "r"(chunk), "h"((uint16_t)3) : "memory");
}
__device__ __forceinline__ void tma_load_3d(uint32_t dst, const CUtensorMap* tm, uint32_t bar, int row, int chunk) {
  asm volatile("cp.async.bulk.tensor.3d.shared::cluster.global.mbarrier::complete_tx::bytes [%0], [%1, {%3, %4, %5}], [%2];" ::"r"(dst), "l"(tm), "r"(bar), "r"(0), "r"(row), "r"(chunk) : "memory");
}
__device__ __forceinline__ void tma_store_2d(const CUtensorMap* tm, uint32_t src, int col, int row) {
  asm volatile("cp.async.bulk.tensor.2d.global.shared::cta.bulk_group [%0, {%2, %3}], [%1];" ::"l"(tm), "r"(src), "r"(col), "r"(row) : "memory");
}
__device__ __forceinline__ void wgmma_fence() { asm volatile("wgmma.fence.sync.aligned;" ::: "memory"); }
__device__ __forceinline__ void wgmma_commit() { asm volatile("wgmma.commit_group.sync.aligned;" ::: "memory"); }
template <int N> __device__ __forceinline__ void wgmma_wait() { asm volatile("wgmma.wait_group.sync.aligned %0;" ::"n"(N) : "memory"); }
__device__ __forceinline__ void fence_async() { asm volatile("fence.proxy.async.global;" ::: "memory"); }
__device__ __forceinline__ void fence_async_smem() { asm volatile("fence.proxy.async.shared::cta;" ::: "memory"); }
__device__ __forceinline__ void cluster_arrive() { asm volatile("barrier.cluster.arrive.release;" ::: "memory"); }
__device__ __forceinline__ void cluster_arrive_relaxed() { asm volatile("barrier.cluster.arrive.relaxed;" ::: "memory"); }
__device__ __forceinline__ void cluster_wait() { asm volatile("barrier.cluster.wait.acquire;" ::: "memory"); }
__device__ __forceinline__ void bar_sync(int id, int n) { asm volatile("bar.sync %0, %1;" ::"r"(id), "r"(n) : "memory"); }
__device__ __forceinline__ void bar_arrive(int id, int n) { asm volatile("bar.arrive %0, %1;" ::"r"(id), "r"(n) : "memory"); }
__device__ __forceinline__ uint32_t ld_relaxed(const unsigned int* p) {
  uint32_t v; asm volatile("ld.relaxed.gpu.global.u32 %0, [%1];" : "=r"(v) : "l"(p) : "memory"); return v;
}
__device__ __forceinline__ void fence_acquire() { asm volatile("fence.acquire.gpu;" ::: "memory"); }
__device__ __forceinline__ void red_release(unsigned int* p) { asm volatile("red.release.gpu.global.add.u32 [%0], 1;" ::"l"(p) : "memory"); }
__device__ __forceinline__ uint32_t launch_epoch() { return ld_relaxed(&g_flags[F_EPOCH + blockIdx.x]) + 1; }
__device__ __forceinline__ void flag_wait(int idx, uint32_t target) {
  uint32_t n = 0;
  target *= launch_epoch();
  while ((int)(ld_relaxed(&g_flags[idx]) - target) < 0) {
    __nanosleep(20);
    if (++n > (1u << 22)) __trap();
  }
  fence_acquire();
}
__device__ __forceinline__ uint32_t pack_bf16(float lo, float hi) {
  uint32_t r; asm("cvt.rn.bf16x2.f32 %0, %1, %2;" : "=r"(r) : "f"(hi), "f"(lo)); return r;
}
__device__ __forceinline__ float bf_lo(uint32_t v) { return __uint_as_float(v << 16); }
__device__ __forceinline__ float bf_hi(uint32_t v) { return __uint_as_float(v & 0xffff0000u); }
__device__ __forceinline__ float ex2(float x) { float r; asm("ex2.approx.ftz.f32 %0, %1;" : "=f"(r) : "f"(x)); return r; }
__device__ __forceinline__ float tanh_fast(float x) { float r; asm("tanh.approx.f32 %0, %1;" : "=f"(r) : "f"(x)); return r; }
__device__ __forceinline__ float gelu2_tanh(float x) {
  float u = x * fmaf(x * x, 0.0356774081f, 0.7978845608f);
  return fmaf(x, tanh_fast(u), x);
}
__device__ __forceinline__ uint32_t mul_bf2(uint32_t a, uint32_t b) { uint32_t r; asm("mul.rn.bf16x2 %0, %1, %2;" : "=r"(r) : "r"(a), "r"(b)); return r; }
__device__ __forceinline__ uint32_t fma_bf2(uint32_t a, uint32_t b, uint32_t c) { uint32_t r; asm("fma.rn.bf16x2 %0, %1, %2, %3;" : "=r"(r) : "r"(a), "r"(b), "r"(c)); return r; }
__device__ __forceinline__ float silu(float y) {
  float r; asm("rcp.approx.ftz.f32 %0, %1;" : "=f"(r) : "f"(1.0f + ex2(-1.4426950409f * y)));
  return y * r;
}
__device__ __forceinline__ void stmatrix_x4(uint32_t addr, uint32_t r0, uint32_t r1, uint32_t r2, uint32_t r3) {
  asm volatile("stmatrix.sync.aligned.m8n8.x4.shared.b16 [%0], {%1, %2, %3, %4};" ::"r"(addr), "r"(r0), "r"(r1), "r"(r2), "r"(r3) : "memory");
}
__device__ __forceinline__ void ldmatrix_x4(uint32_t addr, uint32_t& r0, uint32_t& r1, uint32_t& r2, uint32_t& r3) {
  asm volatile("ldmatrix.sync.aligned.m8n8.x4.shared.b16 {%0, %1, %2, %3}, [%4];" : "=r"(r0), "=r"(r1), "=r"(r2), "=r"(r3) : "r"(addr) : "memory");
}

#define PROF(slot)
#define PROFT(slot, thr)
#define PROFG(slot)

struct Ctx {
  uint32_t sbase;
  uint32_t d16;
  uint32_t rel;
  uint32_t bars;
  uint32_t it;
  uint32_t sc;
  uint32_t stg;
  uint32_t st_off;
  uint32_t st_sw;
  int wg, t;
  int one;
};
__device__ __forceinline__ uint32_t stage_addr(const Ctx& c, uint32_t it) { return c.sbase + (it & 3) * STAGE_BYTES; }
__device__ __forceinline__ void wait_full(const Ctx& c, uint32_t it) { mbar_wait(c.bars + 8 * (it & 3), (it >> 2) & 1); }
__device__ __forceinline__ void release(const Ctx& c, uint32_t it) {
  if (c.t < 2) asm volatile("mbarrier.arrive.shared::cluster.b64 _, [%0];" ::"r"(c.rel + 8 * (it & 3)) : "memory");
}
__device__ __forceinline__ uint64_t desc_of(uint32_t lo) {
  uint64_t d; asm volatile("mov.b64 %0, {%1, %2};" : "=l"(d) : "r"(lo), "r"(0x40000040)); return d;
}
__device__ __forceinline__ uint32_t desc_lo(const Ctx& c, uint32_t addr, uint32_t lbo) { return (addr >> 4) - c.d16 + ((lbo >> 4) << 16); }
template <bool INIT>
__device__ __forceinline__ void mma_step(const Ctx& c, float (&accA)[64], float (&accB)[64], uint32_t it) {
  const uint32_t st = desc_lo(c, c.sbase, 0) + (it & 3) * (STAGE_BYTES >> 4);
  const uint64_t da = desc_of(st + c.wg * 512 + (1 << 16)), db = desc_of(st + 1024 + (512 << 16));
  wgmma_fence();
#pragma unroll
  for (int kk = 0; kk < 4; kk++) wgmma_ss_n256(accA, accB, da + kk * 2, db + kk * 128, (INIT && kk == 0) ? 0 : 1);
  wgmma_commit();
}
__device__ __forceinline__ void stg_acquire(const Ctx& c) { mbar_wait(c.bars + 80 + c.wg * 8, (c.sc & 1) ^ 1); }
__device__ __forceinline__ void stg_commit(Ctx& c) {
  __syncwarp();
  if ((c.t & 31) == 0) mbar_arrive(c.bars + 64 + c.wg * 8);
  c.sc++;
}
template <int OFF>
__device__ __forceinline__ void box_write(const Ctx& c, uint32_t base, const uint32_t (&t)[64]) {
#pragma unroll
  for (int kk = 0; kk < 4; kk++)
    stmatrix_x4(base + c.st_off + (((kk * 2) ^ c.st_sw) << 4), t[OFF + 4 * kk], t[OFF + 4 * kk + 1], t[OFF + 4 * kk + 2], t[OFF + 4 * kk + 3]);
}
__device__ __forceinline__ void acc_write(const Ctx& c, uint32_t base, const float (&s)[64]) {
#pragma unroll
  for (int kk = 0; kk < 8; kk++)
    stmatrix_x4(base + (kk >> 2) * 8192 + c.st_off + ((((kk & 3) * 2) ^ c.st_sw) << 4), pack_bf16(s[8 * kk], s[8 * kk + 1]),
                pack_bf16(s[8 * kk + 2], s[8 * kk + 3]), pack_bf16(s[8 * kk + 4], s[8 * kk + 5]), pack_bf16(s[8 * kk + 6], s[8 * kk + 7]));
}
__device__ __forceinline__ uint32_t opaque(uint32_t v) { asm volatile("" : "+r"(v)); return v; }
__device__ __forceinline__ void half_store(Ctx& c, uint32_t (&t)[64]) {
  stg_acquire(c);
  const uint32_t stg = opaque(c.stg);
  box_write<0>(c, stg, t);
  box_write<16>(c, stg + 8192, t);
  fence_async_smem();
  stg_commit(c);
#pragma unroll
  for (int i = 0; i < 32; i++) asm volatile("mov.b32 %0, %1;" : "=r"(t[i]) : "r"(t[i + 32]));
}
__device__ __forceinline__ void final_half(const Ctx& c, const float (&acc)[64], uint32_t a, uint32_t pitch, const CUtensorMap* m, int col, int row) {
  uint32_t g[32];
#pragma unroll
  for (int kk = 0; kk < 8; kk++)
    ldmatrix_x4(a + (kk >> 2) * pitch + c.st_off + ((((kk & 3) * 2) ^ c.st_sw) << 4), g[4 * kk], g[4 * kk + 1], g[4 * kk + 2], g[4 * kk + 3]);
#pragma unroll
  for (int i = 0; i < 32; i++) g[i] = pack_bf16(acc[2 * i] * bf_lo(g[i]), acc[2 * i + 1] * bf_hi(g[i]));
#pragma unroll
  for (int kk = 0; kk < 8; kk++)
    stmatrix_x4(a + (kk >> 2) * pitch + c.st_off + ((((kk & 3) * 2) ^ c.st_sw) << 4), g[4 * kk], g[4 * kk + 1], g[4 * kk + 2], g[4 * kk + 3]);
  fence_async_smem();
  bar_sync(3 + c.wg, 128);
  if (c.t == 0) {
    fence_async();
    asm volatile("cp.reduce.async.bulk.tensor.2d.global.shared::cta.add.bulk_group [%0, {%2, %3}], [%1];" ::"l"(m), "r"(a), "r"(col), "r"(row) : "memory");
    asm volatile("cp.reduce.async.bulk.tensor.2d.global.shared::cta.add.bulk_group [%0, {%2, %3}], [%1];" ::"l"(m), "r"(a + pitch), "r"(col + 64), "r"(row) : "memory");
    asm volatile("cp.async.bulk.commit_group;" ::: "memory");
  }
}
__device__ __forceinline__ void rotate16(uint32_t (&t)[64]) {
#pragma unroll
  for (int i = 0; i < 16; i++)
    asm volatile("{\n.reg .b32 v;\nmov.b32 v, %0;\nmov.b32 %0, %1;\nmov.b32 %1, %2;\nmov.b32 %2, %3;\nmov.b32 %3, v;\n}\n"
                 : "+r"(t[i]), "+r"(t[i + 16]), "+r"(t[i + 32]), "+r"(t[i + 48]));
}
__device__ __forceinline__ float quad_rcp_sum(float l) {
  l += __shfl_xor_sync(0xffffffffu, l, 1);
  l += __shfl_xor_sync(0xffffffffu, l, 2);
  float r; asm("rcp.approx.ftz.f32 %0, %1;" : "=f"(r) : "f"(l));
  return r;
}
template <int OFF>
__device__ __forceinline__ void capture_plain(uint32_t (&d)[64], const float (&s)[64]) {
#pragma unroll
  for (int i = 0; i < 32; i++) d[OFF + i] = pack_bf16(s[2 * i], s[2 * i + 1]);
}
template <int OFF>
__device__ __forceinline__ void capture_scaled(uint32_t (&d)[64], const float (&s)[64], float r0, float r1) {
#pragma unroll
  for (int i = 0; i < 32; i++) { const float r = (i & 1) ? r1 : r0; d[OFF + i] = pack_bf16(s[2 * i] * r, s[2 * i + 1] * r); }
}
template <int OFF>
__device__ __forceinline__ void capture_gate(uint32_t (&d)[64], const float (&s)[64], float b0, float b1) {
#pragma unroll
  for (int i = 0; i < 32; i++) {
    const float b = (i & 1) ? b1 : b0;
    d[OFF + i] = mul_bf2(pack_bf16(fmaf(s[2 * i], 0.5f, b), fmaf(s[2 * i + 1], 0.5f, b)), d[OFF + i]);
  }
}
template <int K0, int K1>
__device__ __forceinline__ void issue_qk(const Ctx& c, float (&s)[64], uint32_t qaddr, uint32_t it, int z = 0) {
  const uint64_t da = desc_of(desc_lo(c, qaddr, 16) + z), db = desc_of(desc_lo(c, c.sbase, 16) + (it & 3) * (STAGE_BYTES >> 4) + z);
  wgmma_fence();
#pragma unroll
  for (int kk = K0; kk < K1; kk++) wgmma_ss_n128<0>(s, da + (kk >> 2) * 512 + (kk & 3) * 2, db + (kk >> 2) * 1024 + (kk & 3) * 2, kk == 0 ? 0 : 1);
  wgmma_commit();
}
template <int K0, int K1>
__device__ __forceinline__ void issue_pv(const Ctx& c, float (&o)[64], uint32_t paddr, uint32_t it, int first_scale, int z = 0) {
  const uint64_t da = desc_of(desc_lo(c, paddr, 16) + z), db = desc_of(desc_lo(c, c.sbase, 16384) + (it & 3) * (STAGE_BYTES >> 4) + z);
  wgmma_fence();
#pragma unroll
  for (int kk = K0; kk < K1; kk++) wgmma_ss_n128<1>(o, da + (kk >> 2) * 512 + (kk & 3) * 2, db + kk * 128, kk == 0 ? first_scale : 1);
  wgmma_commit();
}
constexpr float SM_SCALE = 0.08838834764831845f * 1.4426950408889634f;
__device__ __forceinline__ void row_max(const float (&s)[64], int t0, int t1, float& x0, float& x1) {
  t0 = max(t0, __shfl_xor_sync(0xffffffffu, t0, 1)); t1 = max(t1, __shfl_xor_sync(0xffffffffu, t1, 1));
  t0 = max(t0, __shfl_xor_sync(0xffffffffu, t0, 2)); t1 = max(t1, __shfl_xor_sync(0xffffffffu, t1, 2));
  if (__builtin_expect(__any_sync(0xffffffffu, t0 == 0 || t1 == 0), 0)) {
    uint32_t u0 = 0xffffffffu, u1 = 0xffffffffu;
#pragma unroll
    for (int i = 0; i < 64; i += 4) {
      u0 = __vimin3_u32(u0, __float_as_uint(s[i]), __float_as_uint(s[i + 1]));
      u1 = __vimin3_u32(u1, __float_as_uint(s[i + 2]), __float_as_uint(s[i + 3]));
    }
    u0 = min(u0, __shfl_xor_sync(0xffffffffu, u0, 1)); u1 = min(u1, __shfl_xor_sync(0xffffffffu, u1, 1));
    u0 = min(u0, __shfl_xor_sync(0xffffffffu, u0, 2)); u1 = min(u1, __shfl_xor_sync(0xffffffffu, u1, 2));
    if (t0 == 0) t0 = (int)u0;
    if (t1 == 0) t1 = (int)u1;
  }
  x0 = __int_as_float(t0); x1 = __int_as_float(t1);
}
struct Att {
  float n0, n1, l0, l1, r0, r1;
  uint32_t it, pb, qb;
  bool rescale, landed;
};
template <int K0, int K1, int C0, int C1>
__device__ __forceinline__ void prob_part(const float (&s)[64], Att& a, const float (&sn)[64], int (&top)[2], uint32_t (&pk)[32]) {
#pragma unroll
  for (int kk = K0; kk < K1; kk++) {
    float e[8];
#pragma unroll
    for (int i = 0; i < 8; i++) asm volatile("ex2.approx.ftz.f32 %0, %1;" : "=f"(e[i]) : "f"(fmaf(s[8 * kk + i], SM_SCALE, (i & 2) ? a.n1 : a.n0)));
    a.l0 += (e[0] + e[1]) + (e[4] + e[5]);
    a.l1 += (e[2] + e[3]) + (e[6] + e[7]);
#pragma unroll
    for (int i = 0; i < 4; i++) asm volatile("cvt.rn.bf16x2.f32 %0, %1, %2;" : "=r"(pk[4 * kk + i]) : "f"(e[2 * i + 1]), "f"(e[2 * i]));
  }
#pragma unroll
  for (int i = 8 * C0; i < 8 * C1; i += 2)
    top[(i >> 1) & 1] = __vimax3_s32(top[(i >> 1) & 1], __float_as_int(sn[i]), __float_as_int(sn[i + 1]));
  asm volatile("" : "+f"(a.l0), "+f"(a.l1), "+r"(top[0]), "+r"(top[1]));
}
#define AS1 2
#define AS2 7
#define RARE(cond) __builtin_expect(!!(cond), 0)
#define ONCE(body) { int rep_ = 0; _Pragma("unroll 1") do { body; } while (++rep_ < c.one); }
template <int MODE, bool ODD>
__device__ __forceinline__ void att_step(Ctx& c, Att& a, int j, float (&s)[64], float (&sn)[64], float (&o)[64]) {
  int top[2] = {0, 0};
  uint32_t pk[32];
  const uint32_t itk = a.it + 1, itv = a.it + (MODE == 1 ? 2 : 1);
  a.it = itv;
  if (MODE != 0) {
    if (RARE(!a.landed)) {
      if (MODE == 1) wait_full(c, itk);
      wait_full(c, itv);
    }
    fence_async_smem();
    if (MODE == 1 && ODD && RARE(j == 5)) stg_commit(c);
    bar_sync(1 + c.wg, 256);
    if (MODE == 1) ONCE((issue_qk<0, 8>(c, sn, j < 3 ? c.stg : a.qb, itk, rep_)))
    else ONCE((issue_pv<0, 8>(c, o, a.pb, itv, 1, rep_), bar_arrive(2 - c.wg, 256)));
  }
  prob_part<0, AS1, 0, 0>(s, a, sn, top, pk);
  if (MODE == 1) ONCE((issue_pv<0, 8>(c, o, a.pb, itv, (j - 1) & 3, rep_), bar_arrive(2 - c.wg, 256)));
  if (MODE == 1) { wgmma_wait<1>(); release(c, itk); }
  prob_part<AS1, AS2, 0, MODE == 1 ? 8 : 0>(s, a, sn, top, pk);
  ONCE(wgmma_wait<0>());
  release(c, itv);
  if (MODE == 0) wait_full(c, itv + 1 + c.wg);
  if (MODE == 1 && !ODD && RARE(j == 6)) { stg_acquire(c); a.pb = c.stg; }
#pragma unroll
  for (int kk = 0; kk < AS2; kk++)
    stmatrix_x4(a.pb + (kk >> 2) * 8192 + c.st_off + ((((kk & 3) * 2) ^ c.st_sw) << 4), pk[4 * kk], pk[4 * kk + 1], pk[4 * kk + 2], pk[4 * kk + 3]);
  if (MODE != 2) a.landed = mbar_test2(c.bars + 8 * ((itv + 1) & 3), ((itv + 1) >> 2) & 1, c.bars + 8 * ((itv + 2) & 3), ((itv + 2) >> 2) & 1);
  prob_part<AS2, 8, 0, MODE == 0 ? 8 : 0>(s, a, sn, top, pk);
#pragma unroll
  for (int kk = AS2; kk < 8; kk++)
    stmatrix_x4(a.pb + (kk >> 2) * 8192 + c.st_off + ((((kk & 3) * 2) ^ c.st_sw) << 4), pk[4 * kk], pk[4 * kk + 1], pk[4 * kk + 2], pk[4 * kk + 3]);
  const float t0 = (16.f - a.n0) * (1.f / SM_SCALE), t1 = (16.f - a.n1) * (1.f / SM_SCALE);
  const bool over = MODE != 2 && __any_sync(0xffffffffu, top[0] > __float_as_int(t0) || top[1] > __float_as_int(t1));
  const bool renew = MODE != 2 && ((ODD && j == 3) || over);
  if (!RARE(renew || (MODE != 0 && a.rescale))) return;
  if (MODE != 0 && a.rescale) {
#pragma unroll
    for (int i = 0; i < 16; i++) { o[4 * i] *= a.r0; o[4 * i + 1] *= a.r0; o[4 * i + 2] *= a.r1; o[4 * i + 3] *= a.r1; }
    a.rescale = false;
    if (MODE == 1 && !ODD && j == 4) acc_write(c, c.stg, o);
  }
  if (renew) {
    float x0, x1;
    row_max(sn, top[0], top[1], x0, x1);
    x0 *= -SM_SCALE; x1 *= -SM_SCALE;
    if (ODD && j == 3) {
      a.r0 = quad_rcp_sum(a.l0); a.r1 = quad_rcp_sum(a.l1);
      a.l0 = 0.f; a.l1 = 0.f;
    } else {
      x0 = fminf(x0, a.n0); x1 = fminf(x1, a.n1);
      a.r0 = ex2(x0 - a.n0); a.r1 = ex2(x1 - a.n1);
      a.l0 *= a.r0; a.l1 *= a.r1;
    }
    a.n0 = x0; a.n1 = x1;
    a.rescale = true;
  }
}

__device__ __forceinline__ void ln_stats(uint32_t (&t)[64], float& r0, float& b0, float& r1, float& b1, uint32_t zero) {
  float m0 = 0.f, m1 = 0.f;
#pragma unroll
  for (int i = 0; i < 16; i++) { m0 += bf_lo(t[i]) + bf_hi(t[i]); m1 += bf_lo(t[16 + i]) + bf_hi(t[16 + i]); }
#pragma unroll
  for (int o = 16; o > 0; o >>= 1) { m0 += __shfl_xor_sync(0xffffffffu, m0, o); m1 += __shfl_xor_sync(0xffffffffu, m1, o); }
  m0 *= 1.0f / DM; m1 *= 1.0f / DM;
#pragma unroll
  for (int i = 0; i < 32; i++) asm volatile("xor.b32 %0, %0, %1;" : "+r"(t[i]) : "r"(zero));
  float q0 = 0.f, q1 = 0.f;
#pragma unroll
  for (int i = 0; i < 16; i++) {
    const float a = bf_lo(t[i]) - m0, b = bf_hi(t[i]) - m0, c = bf_lo(t[16 + i]) - m1, d = bf_hi(t[16 + i]) - m1;
    q0 = fmaf(a, a, fmaf(b, b, q0)); q1 = fmaf(c, c, fmaf(d, d, q1));
  }
#pragma unroll
  for (int o = 16; o > 0; o >>= 1) { q0 += __shfl_xor_sync(0xffffffffu, q0, o); q1 += __shfl_xor_sync(0xffffffffu, q1, o); }
  r0 = rsqrtf(q0 * (1.0f / DM) + 1e-5f); b0 = -m0 * r0;
  r1 = rsqrtf(q1 * (1.0f / DM) + 1e-5f); b1 = -m1 * r1;
}
__device__ __forceinline__ uint32_t ln_apply(uint32_t w, float r, float b) { return pack_bf16(fmaf(bf_lo(w), r, b), fmaf(bf_hi(w), r, b)); }
__device__ __forceinline__ void ln_fixup(float (&acc)[64], uint32_t csum, float r0, float b0, float r1, float b1) {
#pragma unroll
  for (int j = 0; j < 16; j++) {
    float c0, c1;
    asm volatile("ld.shared.v2.f32 {%0, %1}, [%2];" : "=f"(c0), "=f"(c1) : "r"(csum + j * 32) : "memory");
    acc[4 * j] = fmaf(acc[4 * j], r0, b0 * c0); acc[4 * j + 1] = fmaf(acc[4 * j + 1], r0, b0 * c1);
    acc[4 * j + 2] = fmaf(acc[4 * j + 2], r1, b1 * c0); acc[4 * j + 3] = fmaf(acc[4 * j + 3], r1, b1 * c1);
  }
}

__device__ __forceinline__ unsigned long long tag_pack(float u, float v, uint32_t tag) {
  return ((unsigned long long)((__float_as_uint(u) + 128) >> 8) << 40) | ((unsigned long long)((__float_as_uint(v) + 128) >> 8) << 16) | tag;
}
__device__ __forceinline__ float4 tag_gather(const ulonglong2* src, int stride, int n, uint32_t tag) {
  float4 a = make_float4(0.f, 0.f, 0.f, 0.f);
  uint32_t spins = 0;
#pragma unroll 1
  for (int r = 0; r < n;) {
    unsigned long long u[8];
#pragma unroll
    for (int i = 0; i < 4; i++) {
      u[2 * i] = u[2 * i + 1] = tag;
      if (r + i < n) asm volatile("ld.relaxed.gpu.global.v2.u64 {%0, %1}, [%2];" : "=l"(u[2 * i]), "=l"(u[2 * i + 1]) : "l"(src + (r + i) * stride) : "memory");
    }
    bool ok = true;
#pragma unroll
    for (int i = 0; i < 8; i++) ok = ok && ((uint32_t)u[i] & 0xffffu) == tag;
    if (__all_sync(0xffffffffu, ok)) {
#pragma unroll
      for (int i = 0; i < 4; i++) {
        a.x += __uint_as_float((uint32_t)(u[2 * i] >> 32) & 0xffffff00u); a.y += __uint_as_float((uint32_t)(u[2 * i] >> 8) & 0xffffff00u);
        a.z += __uint_as_float((uint32_t)(u[2 * i + 1] >> 32) & 0xffffff00u); a.w += __uint_as_float((uint32_t)(u[2 * i + 1] >> 8) & 0xffffff00u);
      }
      r += 4;
    } else if (++spins > (1u << 22)) __trap();
  }
  return a;
}

struct Prod {
  uint32_t sbase, bars, it, rank, lane;
};
__device__ __forceinline__ uint32_t prod_acquire(Prod& p, uint32_t bytes) {
  uint32_t s = p.it & 3;
  mbar_wait_idle(p.bars + 32 + 8 * s, ((p.it >> 2) & 1) ^ 1);
  if (p.lane == 0) mbar_expect_tx(p.bars + 8 * s, bytes);
  p.it++;
  return s;
}
__device__ __forceinline__ void dep_wait(const Prod& p, uint32_t& ready, int base, int n, uint32_t target, int i) {
  if ((ready >> i) & 1) return;
  target *= launch_epoch();
  uint32_t spins = 0;
  do {
    const bool ok = (int)p.lane < n && (int)(ld_relaxed(&g_flags[base + p.lane]) - target) >= 0;
    ready = __ballot_sync(0xffffffffu, ok);
    if (++spins > (1u << 22)) __trap();
  } while (!((ready >> i) & 1));
  fence_acquire();
  __syncwarp();
  fence_async();
}
__device__ __forceinline__ void prod_gemm(Prod& p, const CUtensorMap* mA, int arow, const CUtensorMap* mB, int chunk, int k0, int k1,
                                          int base, int n, uint32_t target, int shift, uint32_t& ready) {
#pragma unroll 1
  for (int k = k0; k < k1; k++) {
    dep_wait(p, ready, base, n, target, k >> shift);
    uint32_t s = prod_acquire(p, STAGE_BYTES);
    uint32_t a = p.sbase + s * STAGE_BYTES;
    if (p.lane == 0) {
      tma_load_3d_mc(a + 16384 + p.rank * 16384, mB, p.bars + 8 * s, k * 64, chunk + p.rank * 2);
      tma_load_2d(a, mA, p.bars + 8 * s, k * 64, arow);
    }
  }
}

#define CTA_ROLE                                                   \
  uint32_t cta_;                                                   \
  asm volatile("mov.u32 %0, %%ctaid.x;" : "=r"(cta_));             \
  const int role = ((cta_ >> 1) - (cta_ >> 4)) & 7, mb = (cta_ >> 4) * 2 + (cta_ & 1)

__global__ void __cluster_dims__(2, 1, 1) __launch_bounds__(384, 1) mega_kernel(const __grid_constant__ Params P) {
  extern __shared__ __align__(1024) uint8_t smem_raw[];
  const uint32_t sbase = smem_u32(smem_raw);
  const uint32_t bars = sbase + SM_BAR;
  const int tid = threadIdx.x, lane = tid & 31;
  const int wg = __shfl_sync(0xffffffffu, tid >> 7, 0);
  const uint32_t rank = blockIdx.x & 1;
  PROFG(60); PROF(61);

  if (tid == 256) {
    for (int s = 0; s < STAGES; s++) { mbar_init(bars + 8 * s, 1); mbar_init(bars + 32 + 8 * s, 4); }
    for (int w = 0; w < 2; w++) { mbar_init(bars + 64 + 8 * w, 4); mbar_init(bars + 80 + 8 * w, 1); mbar_init(bars + 96 + 8 * w, 5); mbar_init(bars + 112 + 8 * w, 4); }
    for (int w = 0; w < 2; w++) { mbar_init(bars + 144 + 8 * w, 1); }
    mbar_init(bars + 136, 1);
    mbar_init(bars + 160, 8);
    mbar_init(bars + 168, 3);
    mbar_init(bars + 176, 1);
    mbar_init(bars + 184, 1);
    asm volatile("fence.mbarrier_init.release.cluster;" ::: "memory");
  }

  __syncwarp();
  cluster_arrive_relaxed();

  if (wg == 2) {
    const int warp = __shfl_sync(0xffffffffu, tid >> 5, 0);
    CTA_ROLE;
    if (warp == 9 && lane < M_COUNT) asm volatile("prefetch.tensormap [%0];" ::"l"(&P.maps[lane]) : "memory");
    asm volatile("setmaxnreg.dec.sync.aligned.u32 40;");
    const uint32_t task0 = opaque(P.tasks[role][0]);
    cluster_wait();
    if (warp == 8) {
      Prod p{sbase, bars, 0, rank, (uint32_t)lane};
      {
        const uint32_t task = __shfl_sync(0xffffffffu, task0, 0);
        uint32_t ready = 0xffffffffu;
        prod_gemm(p, &P.maps[M_X], mb * 128, &P.maps[(task & 15) == T_QA ? M_WQ : M_WIN],
                  ((task & 15) == T_Z2 ? FH / 64 : 0) + (task >> 4) * 4, 0, STAGES, 0, 0, 0, 5, ready);
      }
      PROFT(43, 256);
#pragma unroll 1
      for (int ti = 0; ti < MAXT; ti++) {
        const uint32_t task = P.tasks[role][ti];
        const int type = task & 15, idx = task >> 4;
        if (type == T_NONE) break;
        const int arow = mb * 128;
        int mA = M_XN, mB = M_WIN, chunk = idx * 4, nk = 16, base = F_XN + mb, n = 1, shift = 5;
        uint32_t target = 8;
        int k0 = 0;
        if (type == T_Z2) chunk += FH / 64;
        else if (type == T_QA) mB = M_WQ;
        else if (type == T_G) { mA = M_WSP; mB = M_Z2; nk = 32; base = F_Z2N; n = 16; target = 14; shift = 1; }
        else if (type == T_S) { mA = M_O_LD; mB = M_WO; k0 = P.krange[role][0]; nk = P.krange[role][1]; base = F_O + mb * 32; n = 32; target = 2; shift = 1; }
        else if (type == T_Y) { mA = M_H_LD; mB = M_WOUT; nk = 28; base = F_H + mb * 8; n = 7; target = 2; shift = 2; }
        if (ti == 0) { mA = M_X; n = 0; k0 = STAGES; }
        uint32_t ready = n ? 0 : 0xffffffffu;
        prod_gemm(p, &P.maps[mA], arow, &P.maps[mB], chunk, k0, nk, base, n, target, shift, ready);
        if (type == T_QA) {
          const int kvrow = (idx >> 2) * SK + (SK - WIN);
#pragma unroll 1
          for (int j = 0; j < 16; j++) {
            const bool isK = j < 2 || (j < 14 && !(j & 1));
            const int ch = (j < 2 ? j : j >= 14 ? j - 12 : isK ? (j >> 1) + 1 : (j >> 1) - 1) & 3;
            uint32_t s = prod_acquire(p, 32768);
            if (lane == 0) tma_load_2d_mc(sbase + s * STAGE_BYTES + rank * 16384, &P.maps[isK ? M_K : M_V], bars + 8 * s, rank * 64, kvrow + ch * 128);
          }
        }
        if (type == T_S) {
          ready = 0;
          dep_wait(p, ready, F_SY + mb * 4 + idx, 1, 2, 0);
          const uint32_t s = prod_acquire(p, 32768);
          if (lane < 2) tma_load_2d(sbase + s * STAGE_BYTES + lane * 16384, &P.maps[M_SY_LD], bars + 8 * s, idx * 256 + 128 + lane * 64, arow);
        }
      }
    } else if (warp == 9 || warp == 10) {
      const int w = warp - 9;
      {
        const uint32_t task = P.tasks[role][0];
        const int type = task & 15, tile = type == T_Z2 ? task >> 4 : 7;
        const uint32_t slab = sbase + SM_STG + w * 16384;
        const uint32_t tag = launch_epoch() & 0xffffu;
        mbar_wait(bars + 136, 0);
        if (lane == 0) {
          const size_t off = (size_t)(blockIdx.x * 16 + w * 8) * DM;
          mbar_expect_tx(bars + 176 + 8 * w, 16384);
          asm volatile("cp.async.bulk.shared::cluster.global.mbarrier::complete_tx::bytes [%0], [%1], 16384, [%2];" ::"r"(slab), "l"(P.x + off), "r"(bars + 176 + 8 * w) : "memory");
          mbar_wait(bars + 96 + 8 * w, 0);
          fence_async_smem();
          mbar_expect_tx(bars + 176 + 8 * w, 16384);
          tma_load_3d(slab, &P.maps[type == T_QA ? M_WQ : M_WIN], bars + 176 + 8 * w, mb * 64, (type == T_Z2 ? FH / 64 : 0) + (task >> 4) * 4 + w * 2);
        }
        __syncwarp();
        mbar_wait(bars + 176 + 8 * w, 1);
        float4 a = make_float4(0.f, 0.f, 0.f, 0.f);
#pragma unroll 1
        for (int r = 0; r < 64; r += 8) {
          uint32_t v0[8], v1[8];
#pragma unroll
          for (int i = 0; i < 8; i++)
            asm volatile("ld.shared.v2.b32 {%0, %1}, [%2];" : "=r"(v0[i]), "=r"(v1[i]) : "r"(slab + (lane >> 4) * 8192 + (r + i) * 128 + ((((lane & 15) >> 1) ^ i) << 4) + (lane & 1) * 8) : "memory");
#pragma unroll
          for (int i = 0; i < 8; i += 2) {
            a.x += bf_lo(v0[i]) + bf_lo(v0[i + 1]); a.y += bf_hi(v0[i]) + bf_hi(v0[i + 1]);
            a.z += bf_lo(v1[i]) + bf_lo(v1[i + 1]); a.w += bf_hi(v1[i]) + bf_hi(v1[i + 1]);
          }
        }
        asm volatile("st.relaxed.gpu.global.v2.u64 [%0], {%1, %2};" ::"l"(&g_csum[(tile * 16 + mb) * 64 + w * 32 + lane]), "l"(tag_pack(a.x, a.y, tag)), "l"(tag_pack(a.z, a.w, tag)) : "memory");
        a = tag_gather(&g_csum[tile * 16 * 64 + w * 32 + lane], 64, 16, tag);
        asm volatile("st.shared.v4.f32 [%0], {%1, %2, %3, %4};" ::"r"(sbase + SM_CSUM + w * 512 + lane * 16), "f"(a.x), "f"(a.y), "f"(a.z), "f"(a.w) : "memory");
        __syncwarp();
        if (lane == 0) mbar_arrive(bars + 168);
        PROFT(50, 288);
        if (type == T_Z2) {
          mbar_wait_idle(bars + 112 + 8 * w, 0);
          a = tag_gather(reinterpret_cast<const ulonglong2*>(&g_stats[mb * 128 + w * 64 + lane * 2]), SEQ / 2, 7, tag);
          const float m0 = a.x * (1.0f / FH), m1 = a.z * (1.0f / FH);
          const float q0 = rsqrtf(fmaxf(fmaf(-m0, m0, a.y * (1.0f / FH)), 0.f) + 4e-5f);
          const float q1 = rsqrtf(fmaxf(fmaf(-m1, m1, a.w * (1.0f / FH)), 0.f) + 4e-5f);
          asm volatile("st.shared.v4.b32 [%0], {%1, %2, %3, %4};" ::"r"(sbase + SM_STAT + w * 512 + lane * 16), "r"(pack_bf16(q0, q0)), "r"(pack_bf16(-m0 * q0, -m0 * q0)),
                       "r"(pack_bf16(q1, q1)), "r"(pack_bf16(-m1 * q1, -m1 * q1)) : "memory");
          __syncwarp();
          if (lane == 0) mbar_arrive(bars + 144 + 8 * w);
        }
      }
      if (lane == 0) {
        uint32_t sc = 0;
#pragma unroll 1
        for (int ti = 0; ti < MAXT; ti++) {
          const uint32_t task = P.tasks[role][ti];
          const int type = task & 15, idx = task >> 4;
          if (type == T_NONE) break;
          if (type == T_S) {
            flag_wait(F_SY + mb * 4 + idx, 2);
            fence_async();
            mbar_expect_tx(bars + 176 + 8 * w, 16384);
            tma_load_2d(sbase + SM_STG + w * 16384, &P.maps[M_SY_ST], bars + 176 + 8 * w, idx * 256, mb * 128 + w * 64);
            tma_load_2d(sbase + SM_STG + w * 16384 + 8192, &P.maps[M_SY_ST], bars + 176 + 8 * w, idx * 256 + 64, mb * 128 + w * 64);
            const bf16* po = P.out + (size_t)(mb * 128 + w * 64) * DM + idx * 256;
#pragma unroll 1
            for (int q = 0; q < 64; q++, po += DM)
              asm volatile("prefetch.global.L2 [%0];\nprefetch.global.L2 [%0 + 128];\nprefetch.global.L2 [%0 + 256];\nprefetch.global.L2 [%0 + 384];" ::"l"(po));
          }
          if (type == T_Z1 || type == T_S) continue;
          const int mi = type == T_Z2 ? M_Z2_ST : type == T_QA ? M_O_ST : type == T_G ? M_H_ST : M_SY_ST;
          const int f = type == T_Z2 ? F_Z2N + mb : type == T_QA ? F_O + mb * 32 + idx * 2 : type == T_G ? F_H + mb * 8 + idx : F_SY + mb * 4 + idx;
#pragma unroll 1
          for (int q = 0; q < 2; q++, sc++) {
            mbar_wait_idle(bars + 64 + w * 8, sc & 1);
            tma_store_2d(&P.maps[mi], sbase + SM_STG + w * 16384, idx * 256 + q * 128, mb * 128 + w * 64);
            tma_store_2d(&P.maps[mi], sbase + SM_STG + w * 16384 + 8192, idx * 256 + q * 128 + 64, mb * 128 + w * 64);
            asm volatile("cp.async.bulk.commit_group;" ::: "memory");
            asm volatile("cp.async.bulk.wait_group.read 0;" ::: "memory");
            mbar_arrive(bars + 80 + w * 8);
            if (q == 1 || type == T_QA) {
              asm volatile("cp.async.bulk.wait_group 0;" ::: "memory");
              red_release(&g_flags[f + (type == T_QA ? q : 0)]);
            }
          }
        }
      }
    } else {
      {
        {
          mbar_wait(bars + 136, 0);
          const size_t off = ((size_t)(blockIdx.x >> 5) * SK + (SK - WIN) + (blockIdx.x & 31) * 16) * 128 + lane * 64;
          asm volatile("prefetch.global.L2 [%0];" ::"l"(P.kv[0] + off));
          asm volatile("prefetch.global.L2 [%0];" ::"l"(P.kv[1] + off));
        }
        if (lane == 0) {
          mbar_wait(bars + 176, 0);
          mbar_wait(bars + 184, 0);
          asm volatile("cp.async.bulk.global.shared::cta.bulk_group [%0], [%1], 32768;" ::"l"(P.out + (size_t)blockIdx.x * 16 * DM), "r"(sbase + SM_STG) : "memory");
          asm volatile("cp.async.bulk.commit_group;" ::: "memory");
          asm volatile("cp.async.bulk.wait_group.read 0;" ::: "memory");
          mbar_arrive(bars + 96);
          mbar_arrive(bars + 104);
          asm volatile("cp.async.bulk.wait_group 0;" ::: "memory");
        }
        __syncwarp();
        mbar_wait(bars + 160, 0);
        if (lane == 0) red_release(&g_flags[F_XN + (blockIdx.x >> 3)]);
        __syncwarp();
        if (lane == 0) asm volatile("st.shared.u32 [%0], %1;" ::"r"(bars + 128), "r"(launch_epoch()) : "memory");
        flag_wait(F_XN + mb, 8);
        const float4 u0 = __ldcg(reinterpret_cast<const float4*>(&g_xstat[mb * 128]) + lane);
        const float4 u1 = __ldcg(reinterpret_cast<const float4*>(&g_xstat[mb * 128 + 64]) + lane);
        asm volatile("st.shared.v4.f32 [%0], {%1, %2, %3, %4};" ::"r"(sbase + SM_STAT + lane * 16), "f"(u0.x), "f"(u0.y), "f"(u0.z), "f"(u0.w) : "memory");
        asm volatile("st.shared.v4.f32 [%0], {%1, %2, %3, %4};" ::"r"(sbase + SM_STAT + 512 + lane * 16), "f"(u1.x), "f"(u1.y), "f"(u1.z), "f"(u1.w) : "memory");
        __syncwarp();
        if (lane == 0) mbar_arrive(bars + 168);
        PROFT(42, 352);
      }
    }
  } else {
    asm volatile("setmaxnreg.inc.sync.aligned.u32 232;");
    const int warp = tid >> 5;
    CTA_ROLE;
    uint32_t t[64];
#pragma unroll
    for (int i = 0; i < 64; i++) t[i] = 0;
    cluster_wait();
    PROF(62);

    Ctx c;
    c.sbase = sbase; c.bars = bars; c.it = 0; c.sc = 0; c.wg = wg; c.t = tid & 127; c.one = P.one;
    c.d16 = (sbase & ~0x3FFFFu) >> 4;
    asm volatile("mapa.shared::cluster.u32 %0, %1, %2;" : "=r"(c.rel) : "r"(bars + 32), "r"(tid & 1));
    c.stg = sbase + SM_STG + wg * 16384;
    {
      const int row = (warp & 3) * 16 + ((lane >> 3) & 1) * 8 + (lane & 7);
      c.st_off = row * 128;
      c.st_sw = (lane >> 4) ^ (lane & 7);
    }
    if (wg == 1) bar_arrive(1, 256);
    float accA[64], accB[64];
    int pend = 2, ptype = T_NONE;
    float s0 = 0.f, s1 = 0.f, q0 = 0.f, q1 = 0.f;
    wait_full(c, 0);
    if (tid == 0) mbar_arrive(bars + 136);
    PROF(40);
    mma_step<true>(c, accA, accB, 0);
#pragma unroll 1
    for (int ti = 0;; ti++) {
      const uint32_t task = P.tasks[role][ti];
      const int type = task & 15;
      const bool is_qa = type == T_QA;
      PROF(ti * 4);
      uint32_t it = c.it + 1;
      const uint32_t nk = type == T_G ? 32 : type == T_Y ? 28 : (type == T_S) ? P.krange[role][1] - P.krange[role][0] : 16;
      const uint32_t last = c.it + nk - 1;
      const uint32_t period = type == T_G ? 4 : (ti == 0 || (ptype == T_Y && nk >= 22)) ? 3 : 2;
      const bool raw = ti == 0;
      uint32_t slot = it + (wg ? period >> 1 : 0) + (raw ? LN_DELAY : 0);
#pragma unroll 1
      for (; it < last; it++) {
        wait_full(c, it);
        mma_step<false>(c, accA, accB, it);
        wgmma_wait<1>();
        release(c, it - 1);
        if (it == slot) {
          const uint32_t stat = sbase + SM_STAT + (wg * 64 + (warp & 3) * 16 + (lane >> 2)) * 8;
          slot += period;
          if (pend > 2) {
            if (ptype == T_Y) {
#pragma unroll
              for (int i = 0; i < 16; i++) t[i] = pack_bf16(silu(bf_lo(t[i])), silu(bf_hi(t[i])));
            } else {
#pragma unroll
              for (int i = 0; i < 16; i++) {
                const float a = gelu2_tanh(bf_lo(t[i])), b = gelu2_tanh(bf_hi(t[i]));
                t[i] = pack_bf16(a, b);
                if (i & 1) { s1 += a + b; q1 = fmaf(a, a, fmaf(b, b, q1)); }
                else { s0 += a + b; q0 = fmaf(a, a, fmaf(b, b, q0)); }
              }
            }
            rotate16(t);
            if (pend == 3) {
              if (ptype == T_Z1) {
                const bf16* bp = P.b_sp + mb * 128 + wg * 64 + (warp & 3) * 16 + (lane >> 2);
                s0 = 0.5f * __bfloat162float(bp[0]); s1 = 0.5f * __bfloat162float(bp[8]);
                pend = 1;
              } else if (ptype == T_Z2) {
                slot += period;
#pragma unroll
                for (int o = 1; o < 4; o <<= 1) {
                  s0 += __shfl_xor_sync(0xffffffffu, s0, o); q0 += __shfl_xor_sync(0xffffffffu, q0, o);
                  s1 += __shfl_xor_sync(0xffffffffu, s1, o); q1 += __shfl_xor_sync(0xffffffffu, q1, o);
                }
                if ((lane & 3) < 2) {
                  const uint32_t t0 = P.tasks[role][0];
                  const int row = mb * 128 + wg * 64 + (warp & 3) * 16 + (lane >> 2) + (lane & 1) * 8;
                  uint32_t epoch;
                  asm volatile("ld.shared.u32 %0, [%1];" : "=r"(epoch) : "r"(bars + 128) : "memory");
                  asm volatile("st.relaxed.gpu.global.u64 [%0], %1;" ::"l"(&g_stats[(t0 >> 4) * SEQ + row]),
                               "l"(tag_pack((lane & 1) ? s1 : s0, (lane & 1) ? q1 : q0, epoch & 0xffffu)) : "memory");
                }
                __syncwarp();
                if (lane == 0) mbar_arrive(bars + 112 + 8 * wg);
              }
            }
          } else if (ptype == T_NONE) {
            if (pend == 2) {
              mbar_wait(bars + 176 + 8 * wg, 0);
#pragma unroll
              for (int i = 0; i < 8; i++)
                asm volatile("ld.shared.v4.u32 {%0, %1, %2, %3}, [%4];" : "=r"(t[4 * i]), "=r"(t[4 * i + 1]), "=r"(t[4 * i + 2]), "=r"(t[4 * i + 3]) : "r"(c.stg + (warp & 3) * 4096 + i * 512 + lane * 16) : "memory");
              __syncwarp();
              if (lane == 0) mbar_arrive(bars + 96 + 8 * wg);
              ln_stats(t, s0, q0, s1, q1, t[32]);
            }
            if (pend == 1) {
              const int row = blockIdx.x * 16 + warp * 2;
              uint4* xo = reinterpret_cast<uint4*>(g_xn + (size_t)row * DM);
#pragma unroll
              for (int i = 0; i < 8; i++) {
                const float r = i < 4 ? s0 : s1, b = i < 4 ? q0 : q1;
                xo[i * 32 + lane] = make_uint4(ln_apply(t[4 * i], r, b), ln_apply(t[4 * i + 1], r, b), ln_apply(t[4 * i + 2], r, b), ln_apply(t[4 * i + 3], r, b));
              }
              if (lane == 0) *reinterpret_cast<float4*>(&g_xstat[row]) = make_float4(s0, q0, s1, q1);
              __syncwarp();
              if (lane == 0) mbar_arrive(bars + 160);
              PROF(41);
            }
          } else {
            if (ptype == T_Z2) {
              uint32_t a0, b0, a1, b1;
              mbar_wait(bars + 144 + 8 * wg, 0);
              asm volatile("ld.shared.v2.b32 {%0, %1}, [%2];" : "=r"(a0), "=r"(b0) : "r"(stat) : "memory");
              asm volatile("ld.shared.v2.b32 {%0, %1}, [%2];" : "=r"(a1), "=r"(b1) : "r"(stat + 64) : "memory");
#pragma unroll
              for (int i = 0; i < 32; i++) t[i] = fma_bf2(t[i], (i & 1) ? a1 : a0, (i & 1) ? b1 : b0);
            }
            half_store(c, t);
          }
          if (--pend == 0) slot = last;
        }
      }
      wait_full(c, it);
      if (is_qa) stg_acquire(c);
      bar_sync(1 + wg, 256);
      mma_step<false>(c, accA, accB, it);
      bar_arrive(2 - wg, 256);
      wgmma_wait<1>();
      release(c, it - 1);
      wgmma_wait<0>();
      release(c, it);
      it++;
      PROF(ti * 4 + 1);
      if (type == T_S) {
        const int col = (task >> 4) * 256, row = mb * 128 + wg * 64;
        PROF(44);
        mbar_wait(bars + 176 + 8 * wg, 0);
        PROF(45);
#pragma unroll 1
        for (int h = 0;; h++) {
          final_half(c, accA, h ? stage_addr(c, it) + wg * 8192 : c.stg, h ? 16384 : 8192, &P.maps[M_OUT], col + h * 128, row);
          if (h) break;
          PROF(46);
#pragma unroll
          for (int i = 0; i < 64; i++) accA[i] = accB[i];
          wait_full(c, it);
          PROF(47);
        }
        PROF(48);
        if (c.t == 0) asm volatile("cp.async.bulk.wait_group.read 0;" ::: "memory");
        PROF(ti * 4 + 2);
        break;
      }
      if (raw) {
        const uint32_t stat = sbase + SM_STAT + (wg * 64 + (warp & 3) * 16 + (lane >> 2)) * 8;
        mbar_wait(bars + 168, 0);
        asm volatile("ld.shared.v2.f32 {%0, %1}, [%2];" : "=f"(s0), "=f"(q0) : "r"(stat) : "memory");
        asm volatile("ld.shared.v2.f32 {%0, %1}, [%2];" : "=f"(s1), "=f"(q1) : "r"(stat + 64) : "memory");
        ln_fixup(accA, sbase + SM_CSUM + (lane & 3) * 8, s0, q0, s1, q1);
        ln_fixup(accB, sbase + SM_CSUM + 512 + (lane & 3) * 8, s0, q0, s1, q1);
      }
      if (is_qa) {
        acc_write(c, opaque(c.stg), accA);
        Att a;
        a.qb = stage_addr(c, it + wg) + 32768;
        a.pb = stage_addr(c, it + 2 + wg) + 32768;
        float sa[64], sb[64], o[64];
#pragma unroll
        for (int i = 0; i < 64; i++) { sa[i] = 0.f; sb[i] = 0.f; }
        wait_full(c, it);
        wait_full(c, it + 1);
        fence_async_smem();
        bar_sync(1 + wg, 256);
        issue_qk<0, 8>(c, sa, c.stg, it);
        acc_write(c, a.qb, accB);
        issue_qk<0, 8>(c, sb, c.stg, it + 1);
        bar_arrive(2 - wg, 256);
        wgmma_wait<1>();
        release(c, it);
        a.it = it; a.l0 = 0.f; a.l1 = 0.f; a.r0 = 0.f; a.r1 = 0.f; a.rescale = false;
        {
          float x0, x1;
          int m[4] = {0, 0, 0, 0};
#pragma unroll
          for (int i = 0; i < 64; i += 2) m[(i >> 1) & 3] = __vimax3_s32(m[(i >> 1) & 3], __float_as_int(sa[i]), __float_as_int(sa[i + 1]));
          row_max(sa, max(m[0], m[2]), max(m[1], m[3]), x0, x1);
          a.n0 = -x0 * SM_SCALE; a.n1 = -x1 * SM_SCALE;
        }
        att_step<0, false>(c, a, 0, sa, sb, o);
#pragma unroll
        for (int i = 0; i < 64; i++) o[i] = 0.f;
#pragma unroll 1
        for (int j = 1; j < 7; j += 2) {
          att_step<1, true>(c, a, j, sb, sa, o);
          att_step<1, false>(c, a, j + 1, sa, sb, o);
        }
        att_step<2, true>(c, a, 7, sb, sa, o);
        it = a.it + 1;
        wait_full(c, it);
        fence_async_smem();
        bar_sync(1 + wg, 256);
        issue_pv<0, 8>(c, o, a.pb, it, 1);
        it++;
#pragma unroll
        for (int i = 0; i < 64; i++) { accA[i] = 0.f; accB[i] = 0.f; }
        wait_full(c, it);
        mma_step<true>(c, accA, accB, it);
        bar_arrive(2 - wg, 256);
        const float r0 = quad_rcp_sum(a.l0), r1 = quad_rcp_sum(a.l1);
        wgmma_wait<1>();
        release(c, it - 1);
        capture_scaled<0>(t, o, r0, r1);
#pragma unroll
        for (int i = 32; i < 64; i++) t[i] = 0;
      } else {
        if (type == T_G) {
          capture_gate<0>(t, accA, s0, s1);
          capture_gate<32>(t, accB, s0, s1);
        } else {
          capture_plain<0>(t, accA);
          capture_plain<32>(t, accB);
        }
        wait_full(c, it);
        mma_step<true>(c, accA, accB, it);
      }
      c.it = it;
      s0 = 0.f; s1 = 0.f; q0 = 0.f; q1 = 0.f;
      pend = is_qa ? 1 : (type == T_Z2 || type == T_Z1 || type == T_Y) ? 6 : 2;
      ptype = type;
      PROF(ti * 4 + 2);
      PROF(ti * 4 + 3);
    }
    wgmma_wait<0>();
    PROF(59);
  }
  __syncwarp();
  cluster_arrive_relaxed();
  cluster_wait();
  if (tid == 0) asm volatile("red.relaxed.gpu.global.add.u32 [%0], 1;" ::"l"(&g_flags[F_EPOCH + blockIdx.x]) : "memory");
  PROFG(63);
}

typedef CUresult (*PFN_encodeTiled)(CUtensorMap*, CUtensorMapDataType, cuuint32_t, void*, const cuuint64_t*, const cuuint64_t*, const cuuint32_t*,
                                    const cuuint32_t*, CUtensorMapInterleave, CUtensorMapSwizzle, CUtensorMapL2promotion, CUtensorMapFloatOOBfill);

static void map_2d(PFN_encodeTiled enc, CUtensorMap* m, const void* ptr, uint64_t rows, uint64_t cols, uint32_t box_rows = 128) {
  cuuint64_t dims[2] = {cols, rows}; cuuint64_t strides[1] = {cols * 2};
  cuuint32_t box[2] = {64, box_rows}; cuuint32_t es[2] = {1, 1};
  enc(m, CU_TENSOR_MAP_DATA_TYPE_BFLOAT16, 2, const_cast<void*>(ptr), dims, strides, box, es, CU_TENSOR_MAP_INTERLEAVE_NONE,
      CU_TENSOR_MAP_SWIZZLE_128B, CU_TENSOR_MAP_L2_PROMOTION_L2_256B, CU_TENSOR_MAP_FLOAT_OOB_FILL_NONE);
}
static void map_3d(PFN_encodeTiled enc, CUtensorMap* m, const void* ptr, uint64_t rows, uint64_t cols) {
  cuuint64_t dims[3] = {64, rows, cols / 64}; cuuint64_t strides[2] = {cols * 2, 128};
  cuuint32_t box[3] = {64, 64, 2}; cuuint32_t es[3] = {1, 1, 1};
  enc(m, CU_TENSOR_MAP_DATA_TYPE_BFLOAT16, 3, const_cast<void*>(ptr), dims, strides, box, es, CU_TENSOR_MAP_INTERLEAVE_NONE,
      CU_TENSOR_MAP_SWIZZLE_128B, CU_TENSOR_MAP_L2_PROMOTION_L2_256B, CU_TENSOR_MAP_FLOAT_OOB_FILL_NONE);
}
static unsigned char mk(int type, int idx) { return (unsigned char)(type | (idx << 4)); }

#define SPLIT0 "37"
#define SPLIT1 "40"
#define SPLIT3 "37"
static void build_schedule(Params& P) {
  static const char* const plan[8] = {
      "q0 h1 q9 y0 s0:" SPLIT0 "-64",
      "z0 q1 h2 q12 s0:0-" SPLIT0,
      "z2 q3 q7 q10 y1 s1:" SPLIT1 "-64",
      "z1 q2 h3 q13 s1:0-" SPLIT1,
      "z4 q5 q8 q11 y2 s2:" SPLIT1 "-64",
      "z3 q4 h4 q14 s2:0-" SPLIT1,
      "z6 h0 h6 y3 s3:" SPLIT3 "-64",
      "z5 q6 h5 q15 s3:0-" SPLIT3,
  };
  for (int j = 0; j < 8; j++) {
    unsigned char* T = P.tasks[j];
    int n = 0;
    for (const char* q = plan[j]; *q;) {
      const char kind = *q++;
      int v[3] = {0, 0, 0};
      for (int f = 0; *q && *q != ' '; q++) {
        if (*q == ':' || *q == '-') f++;
        else v[f] = v[f] * 10 + (*q - '0');
      }
      while (*q == ' ') q++;
      if (kind == 'z') T[n++] = mk(T_Z2, v[0]);
      else if (kind == 'q') T[n++] = mk(T_QA, v[0]);
      else if (kind == 'h') { T[n++] = mk(T_Z1, v[0]); T[n++] = mk(T_G, v[0]); }
      else if (kind == 'y') T[n++] = mk(T_Y, v[0]);
      else { T[n++] = mk(T_S, v[0]); P.krange[j][0] = (unsigned char)v[1]; P.krange[j][1] = (unsigned char)v[2]; }
    }
    while (n < MAXT) T[n++] = 0;
  }
}

extern "C" void kernel_launch(void* const* d_in, const int* in_sizes, int n_in, void* d_out, int out_size) {
  (void)in_sizes; (void)n_in; (void)out_size;
  static PFN_encodeTiled enc = nullptr;
  static void *p_xn, *p_z2, *p_o, *p_h, *p_sy;
  if (!enc) {
    void* fn = nullptr; cudaDriverEntryPointQueryResult qr;
    cudaGetDriverEntryPoint("cuTensorMapEncodeTiled", &fn, cudaEnableDefault, &qr);
    enc = (PFN_encodeTiled)fn;
    cudaGetSymbolAddress(&p_xn, g_xn); cudaGetSymbolAddress(&p_z2, g_z2); cudaGetSymbolAddress(&p_o, g_o);
    cudaGetSymbolAddress(&p_h, g_h); cudaGetSymbolAddress(&p_sy, g_sy);
    cudaFuncSetAttribute(mega_kernel, cudaFuncAttributeMaxDynamicSharedMemorySize, SMEM_BYTES);
  }
  Params P;
  map_2d(enc, &P.maps[M_XN], p_xn, SEQ, DM);
  map_2d(enc, &P.maps[M_WSP], d_in[7], SEQ, SEQ);
  map_2d(enc, &P.maps[M_O_LD], p_o, SEQ, HD);
  map_2d(enc, &P.maps[M_H_LD], p_h, SEQ, FH);
  map_2d(enc, &P.maps[M_X], d_in[0], SEQ, DM);
  map_2d(enc, &P.maps[M_SY_LD], p_sy, SEQ, DM);
  map_2d(enc, &P.maps[M_K], d_in[1], 4 * SK, 128);
  map_2d(enc, &P.maps[M_V], d_in[2], 4 * SK, 128);
  map_3d(enc, &P.maps[M_WIN], d_in[6], DM, FF);
  map_3d(enc, &P.maps[M_WQ], d_in[3], DM, HD);
  map_3d(enc, &P.maps[M_Z2], p_z2, SEQ, FH);
  map_3d(enc, &P.maps[M_WO], d_in[4], HD, DM);
  map_3d(enc, &P.maps[M_WOUT], d_in[9], FH, DM);
  map_2d(enc, &P.maps[M_Z2_ST], p_z2, SEQ, FH, 64);
  map_2d(enc, &P.maps[M_O_ST], p_o, SEQ, HD, 64);
  map_2d(enc, &P.maps[M_H_ST], p_h, SEQ, FH, 64);
  map_2d(enc, &P.maps[M_SY_ST], p_sy, SEQ, DM, 64);
  map_2d(enc, &P.maps[M_OUT], d_out, SEQ, DM, 64);
  P.x = (const bf16*)d_in[0];
  P.out = (bf16*)d_out;
  P.b_sp = (const bf16*)d_in[8];
  P.kv[0] = (const bf16*)d_in[1];
  P.kv[1] = (const bf16*)d_in[2];
  P.one = 1;
  build_schedule(P);
  mega_kernel<<<NCLUSTERS * 2, 384, SMEM_BYTES, cudaStreamPerThread>>>(P);
}
```

```cpp
#include <cuda_runtime.h>
#include <cuda_bf16.h>
#include <cuda.h>
#include <stdint.h>

typedef __nv_bfloat16 bf16;

constexpr int SEQ = 2048, DM = 1024, HD = 4096, FF = 3584, FH = 1792, SK = 2048, WIN = 512;
constexpr int NCLUSTERS = 64;
constexpr int MAXT = 8;
constexpr int LN_DELAY = 2;

__device__ bf16 g_xn[SEQ * DM];
__device__ bf16 g_z2[SEQ * FH];
__device__ bf16 g_o[SEQ * HD];
__device__ bf16 g_h[SEQ * FH];
__device__ bf16 g_sy[SEQ * DM];
constexpr int F_XN = 0;
constexpr int F_Z2N = 16;
constexpr int F_O = 64;
constexpr int F_H = 576;
constexpr int F_SY = 704;
constexpr int F_EPOCH = 768;
constexpr int F_COUNT = 1024;
__device__ __align__(16) unsigned int g_flags[F_COUNT];
__device__ float2 g_xstat[SEQ];
__device__ ulonglong2 g_csum[8 * 16 * 64];
__device__ __align__(16) unsigned long long g_stats[8 * SEQ];

enum { M_XN = 0, M_WSP, M_O_LD, M_H_LD, M_X, M_SY_LD, M_K, M_V,
       M_WIN, M_WQ, M_Z2, M_WO, M_WOUT,
       M_Z2_ST, M_O_ST, M_H_ST, M_SY_ST, M_OUT,
       M_COUNT };
enum { T_NONE = 0, T_Z2, T_QA, T_Z1, T_G, T_Y, T_S };

struct Params {
  CUtensorMap maps[M_COUNT];
  const bf16* x;
  bf16* out;
  const bf16* b_sp;
  const bf16* kv[2];
  int one;
  unsigned char tasks[8][MAXT];
  unsigned char krange[8][2];
};

constexpr int STAGES = 4;
constexpr int STAGE_BYTES = 49152;
constexpr int SM_STG = STAGES * STAGE_BYTES;
constexpr int SM_BAR = SM_STG + 32768;
constexpr int SM_STAT = SM_BAR + 256;
constexpr int SM_CSUM = SM_STAT + 1024;
constexpr int SMEM_BYTES = SM_CSUM + 1024;

template <int TB>
__device__ __forceinline__ void wgmma_ss_n128(float (&d)[64], uint64_t da, uint64_t db, int scale_d) {
  asm volatile("{\n.reg .pred p;\nsetp.ne.b32 p, %66, 0;\n"
    "wgmma.mma_async.sync.aligned.m64n128k16.f32.bf16.bf16 {%0, %1, %2, %3, %4, %5, %6, %7, %8, %9, %10, %11, %12, %13, %14, %15, %16, %17, %18, %19, %20, %21, %22, %23, %24, %25, %26, %27, %28, %29, %30, %31, %32, %33, %34, %35, %36, %37, %38, %39, %40, %41, %42, %43, %44, %45, %46, %47, %48, %49, %50, %51, %52, %53, %54, %55, %56, %57, %58, %59, %60, %61, %62, %63}, %64, %65, p, 1, 1, 0, %67;\n}\n"
    : "+f"(d[0]), "+f"(d[1]), "+f"(d[2]), "+f"(d[3]), "+f"(d[4]), "+f"(d[5]), "+f"(d[6]), "+f"(d[7]), "+f"(d[8]), "+f"(d[9]), "+f"(d[10]), "+f"(d[11]), "+f"(d[12]), "+f"(d[13]), "+f"(d[14]), "+f"(d[15]), "+f"(d[16]), "+f"(d[17]), "+f"(d[18]), "+f"(d[19]), "+f"(d[20]), "+f"(d[21]), "+f"(d[22]), "+f"(d[23]), "+f"(d[24]), "+f"(d[25]), "+f"(d[26]), "+f"(d[27]), "+f"(d[28]), "+f"(d[29]), "+f"(d[30]), "+f"(d[31]), "+f"(d[32]), "+f"(d[33]), "+f"(d[34]), "+f"(d[35]), "+f"(d[36]), "+f"(d[37]), "+f"(d[38]), "+f"(d[39]), "+f"(d[40]), "+f"(d[41]), "+f"(d[42]), "+f"(d[43]), "+f"(d[44]), "+f"(d[45]), "+f"(d[46]), "+f"(d[47]), "+f"(d[48]), "+f"(d[49]), "+f"(d[50]), "+f"(d[51]), "+f"(d[52]), "+f"(d[53]), "+f"(d[54]), "+f"(d[55]), "+f"(d[56]), "+f"(d[57]), "+f"(d[58]), "+f"(d[59]), "+f"(d[60]), "+f"(d[61]), "+f"(d[62]), "+f"(d[63])
    : "l"(da), "l"(db), "r"(scale_d), "n"(TB));
}
__device__ __forceinline__ void wgmma_ss_n256(float (&d)[64], float (&e)[64], uint64_t da, uint64_t db, int scale_d) {
  asm volatile("{\n.reg .pred p;\nsetp.ne.b32 p, %130, 0;\n"
    "wgmma.mma_async.sync.aligned.m64n256k16.f32.bf16.bf16 {%0, %1, %2, %3, %4, %5, %6, %7, %8, %9, %10, %11, %12, %13, %14, %15, %16, %17, %18, %19, %20, %21, %22, %23, %24, %25, %26, %27, %28, %29, %30, %31, %32, %33, %34, %35, %36, %37, %38, %39, %40, %41, %42, %43, %44, %45, %46, %47, %48, %49, %50, %51, %52, %53, %54, %55, %56, %57, %58, %59, %60, %61, %62, %63, %64, %65, %66, %67, %68, %69, %70, %71, %72, %73, %74, %75, %76, %77, %78, %79, %80, %81, %82, %83, %84, %85, %86, %87, %88, %89, %90, %91, %92, %93, %94, %95, %96, %97, %98, %99, %100, %101, %102, %103, %104, %105, %106, %107, %108, %109, %110, %111, %112, %113, %114, %115, %116, %117, %118, %119, %120, %121, %122, %123, %124, %125, %126, %127}, %128, %129, p, 1, 1, 0, 1;\n}\n"
    : "+f"(d[0]), "+f"(d[1]), "+f"(d[2]), "+f"(d[3]), "+f"(d[4]), "+f"(d[5]), "+f"(d[6]), "+f"(d[7]), "+f"(d[8]), "+f"(d[9]), "+f"(d[10]), "+f"(d[11]), "+f"(d[12]), "+f"(d[13]), "+f"(d[14]), "+f"(d[15]), "+f"(d[16]), "+f"(d[17]), "+f"(d[18]), "+f"(d[19]), "+f"(d[20]), "+f"(d[21]), "+f"(d[22]), "+f"(d[23]), "+f"(d[24]), "+f"(d[25]), "+f"(d[26]), "+f"(d[27]), "+f"(d[28]), "+f"(d[29]), "+f"(d[30]), "+f"(d[31]), "+f"(d[32]), "+f"(d[33]), "+f"(d[34]), "+f"(d[35]), "+f"(d[36]), "+f"(d[37]), "+f"(d[38]), "+f"(d[39]), "+f"(d[40]), "+f"(d[41]), "+f"(d[42]), "+f"(d[43]), "+f"(d[44]), "+f"(d[45]), "+f"(d[46]), "+f"(d[47]), "+f"(d[48]), "+f"(d[49]), "+f"(d[50]), "+f"(d[51]), "+f"(d[52]), "+f"(d[53]), "+f"(d[54]), "+f"(d[55]), "+f"(d[56]), "+f"(d[57]), "+f"(d[58]), "+f"(d[59]), "+f"(d[60]), "+f"(d[61]), "+f"(d[62]), "+f"(d[63]), "+f"(e[0]), "+f"(e[1]), "+f"(e[2]), "+f"(e[3]), "+f"(e[4]), "+f"(e[5]), "+f"(e[6]), "+f"(e[7]), "+f"(e[8]), "+f"(e[9]), "+f"(e[10]), "+f"(e[11]), "+f"(e[12]), "+f"(e[13]), "+f"(e[14]), "+f"(e[15]), "+f"(e[16]), "+f"(e[17]), "+f"(e[18]), "+f"(e[19]), "+f"(e[20]), "+f"(e[21]), "+f"(e[22]), "+f"(e[23]), "+f"(e[24]), "+f"(e[25]), "+f"(e[26]), "+f"(e[27]), "+f"(e[28]), "+f"(e[29]), "+f"(e[30]), "+f"(e[31]), "+f"(e[32]), "+f"(e[33]), "+f"(e[34]), "+f"(e[35]), "+f"(e[36]), "+f"(e[37]), "+f"(e[38]), "+f"(e[39]), "+f"(e[40]), "+f"(e[41]), "+f"(e[42]), "+f"(e[43]), "+f"(e[44]), "+f"(e[45]), "+f"(e[46]), "+f"(e[47]), "+f"(e[48]), "+f"(e[49]), "+f"(e[50]), "+f"(e[51]), "+f"(e[52]), "+f"(e[53]), "+f"(e[54]), "+f"(e[55]), "+f"(e[56]), "+f"(e[57]), "+f"(e[58]), "+f"(e[59]), "+f"(e[60]), "+f"(e[61]), "+f"(e[62]), "+f"(e[63])
    : "l"(da), "l"(db), "r"(scale_d));
}

__device__ __forceinline__ uint32_t smem_u32(const void* p) { return (uint32_t)__cvta_generic_to_shared(p); }
__device__ __forceinline__ void mbar_init(uint32_t bar, uint32_t cnt) { asm volatile("mbarrier.init.shared::cta.b64 [%0], %1;" ::"r"(bar), "r"(cnt) : "memory"); }
__device__ __forceinline__ void mbar_expect_tx(uint32_t bar, uint32_t bytes) { asm volatile("mbarrier.arrive.expect_tx.shared::cta.b64 _, [%0], %1;" ::"r"(bar), "r"(bytes) : "memory"); }
__device__ __forceinline__ void mbar_arrive(uint32_t bar) { asm volatile("mbarrier.arrive.shared::cta.b64 _, [%0];" ::"r"(bar) : "memory"); }
__device__ __forceinline__ void mbar_wait(uint32_t bar, uint32_t parity) {
  asm volatile(
      "{\n.reg .pred p;\n.reg .u32 n;\nmov.u32 n, 0;\n"
      "LAB_WAIT:\nmbarrier.try_wait.parity.shared::cta.b64 p, [%0], %1;\n@p bra LAB_DONE;\n"
      "add.u32 n, n, 1;\nsetp.lt.u32 p, n, 4194304;\n@p bra LAB_WAIT;\ntrap;\nLAB_DONE:\n}\n" ::"r"(bar), "r"(parity) : "memory");
}
__device__ __forceinline__ void mbar_wait_idle(uint32_t bar, uint32_t parity) {
  asm volatile(
      "{\n.reg .pred p;\n.reg .u32 n;\nmov.u32 n, 0;\n"
      "LAB_WAIT:\nmbarrier.try_wait.parity.shared::cta.b64 p, [%0], %1, 1000;\n@p bra LAB_DONE;\n"
      "add.u32 n, n, 1;\nsetp.lt.u32 p, n, 4194304;\n@p bra LAB_WAIT;\ntrap;\nLAB_DONE:\n}\n" ::"r"(bar), "r"(parity) : "memory");
}
__device__ __forceinline__ bool mbar_test2(uint32_t bar0, uint32_t par0, uint32_t bar1, uint32_t par1) {
  uint32_t ok;
  asm volatile("{\n.reg .pred p, q;\nmbarrier.test_wait.parity.shared::cta.b64 p, [%1], %2;\nmbarrier.test_wait.parity.shared::cta.b64 q, [%3], %4;\n"
               "and.pred p, p, q;\nvote.sync.all.pred p, p, 0xffffffff;\nselp.u32 %0, 1, 0, p;\n}\n" : "=r"(ok) : "r"(bar0), "r"(par0), "r"(bar1), "r"(par1) : "memory");
  return ok != 0;
}
__device__ __forceinline__ void tma_load_2d(uint32_t dst, const CUtensorMap* tm, uint32_t bar, int c0, int c1) {
  asm volatile("cp.async.bulk.tensor.2d.shared::cluster.global.mbarrier::complete_tx::bytes [%0], [%1, {%3, %4}], [%2];" ::"r"(dst), "l"(tm), "r"(bar), "r"(c0), "r"(c1) : "memory");
}
__device__ __forceinline__ void tma_load_2d_mc(uint32_t dst, const CUtensorMap* tm, uint32_t bar, int c0, int c1) {
  asm volatile("cp.async.bulk.tensor.2d.shared::cluster.global.mbarrier::complete_tx::bytes.multicast::cluster [%0], [%1, {%3, %4}], [%2], %5;" ::"r"(dst), "l"(tm), "r"(bar), "r"(c0), "r"(c1), "h"((uint16_t)3) : "memory");
}
__device__ __forceinline__ void tma_load_3d_mc(uint32_t dst, const CUtensorMap* tm, uint32_t bar, int row, int chunk) {
  asm volatile("cp.async.bulk.tensor.3d.shared::cluster.global.mbarrier::complete_tx::bytes.multicast::cluster [%0], [%1, {%3, %4, %5}], [%2], %6;" ::"r"(dst), "l"(tm), "r"(bar), "r"(0), "r"(row), "r"(chunk), "h"((uint16_t)3) : "memory");
}
__device__ __forceinline__ void tma_load_3d(uint32_t dst, const CUtensorMap* tm, uint32_t bar, int row, int chunk) {
  asm volatile("cp.async.bulk.tensor.3d.shared::cluster.global.mbarrier::complete_tx::bytes [%0], [%1, {%3, %4, %5}], [%2];" ::"r"(dst), "l"(tm), "r"(bar), "r"(0), "r"(row), "r"(chunk) : "memory");
}
__device__ __forceinline__ void tma_store_2d(const CUtensorMap* tm, uint32_t src, int col, int row) {
  asm volatile("cp.async.bulk.tensor.2d.global.shared::cta.bulk_group [%0, {%2, %3}], [%1];" ::"l"(tm), "r"(src), "r"(col), "r"(row) : "memory");
}
__device__ __forceinline__ void wgmma_fence() { asm volatile("wgmma.fence.sync.aligned;" ::: "memory"); }
__device__ __forceinline__ void wgmma_commit() { asm volatile("wgmma.commit_group.sync.aligned;" ::: "memory"); }
template <int N> __device__ __forceinline__ void wgmma_wait() { asm volatile("wgmma.wait_group.sync.aligned %0;" ::"n"(N) : "memory"); }
__device__ __forceinline__ void fence_async() { asm volatile("fence.proxy.async.global;" ::: "memory"); }
__device__ __forceinline__ void fence_async_smem() { asm volatile("fence.proxy.async.shared::cta;" ::: "memory"); }
__device__ __forceinline__ void cluster_arrive_relaxed() { asm volatile("barrier.cluster.arrive.relaxed;" ::: "memory"); }
__device__ __forceinline__ void cluster_wait() { asm volatile("barrier.cluster.wait.acquire;" ::: "memory"); }
__device__ __forceinline__ void bar_sync(int id, int n) { asm volatile("bar.sync %0, %1;" ::"r"(id), "r"(n) : "memory"); }
__device__ __forceinline__ void bar_arrive(int id, int n) { asm volatile("bar.arrive %0, %1;" ::"r"(id), "r"(n) : "memory"); }
__device__ __forceinline__ uint32_t ld_relaxed(const unsigned int* p) {
  uint32_t v; asm volatile("ld.relaxed.gpu.global.u32 %0, [%1];" : "=r"(v) : "l"(p) : "memory"); return v;
}
__device__ __forceinline__ void fence_acquire() { asm volatile("fence.acquire.gpu;" ::: "memory"); }
__device__ __forceinline__ void red_release(unsigned int* p) { asm volatile("red.release.gpu.global.add.u32 [%0], 1;" ::"l"(p) : "memory"); }
__device__ __forceinline__ uint32_t launch_epoch() { return ld_relaxed(&g_flags[F_EPOCH + blockIdx.x]) + 1; }
__device__ __forceinline__ void flag_wait(int idx, uint32_t target) {
  uint32_t n = 0;
  target *= launch_epoch();
  while ((int)(ld_relaxed(&g_flags[idx]) - target) < 0) {
    __nanosleep(20);
    if (++n > (1u << 22)) __trap();
  }
  fence_acquire();
}
__device__ __forceinline__ uint32_t pack_bf16(float lo, float hi) {
  uint32_t r; asm("cvt.rn.bf16x2.f32 %0, %1, %2;" : "=r"(r) : "f"(hi), "f"(lo)); return r;
}
__device__ __forceinline__ float bf_lo(uint32_t v) { return __uint_as_float(v << 16); }
__device__ __forceinline__ float bf_hi(uint32_t v) { return __uint_as_float(v & 0xffff0000u); }
__device__ __forceinline__ float ex2(float x) { float r; asm("ex2.approx.ftz.f32 %0, %1;" : "=f"(r) : "f"(x)); return r; }
__device__ __forceinline__ float tanh_fast(float x) { float r; asm("tanh.approx.f32 %0, %1;" : "=f"(r) : "f"(x)); return r; }
__device__ __forceinline__ float gelu2_tanh(float x) {
  float u = x * fmaf(x * x, 0.0356774081f, 0.7978845608f);
  return fmaf(x, tanh_fast(u), x);
}
__device__ __forceinline__ uint32_t mul_bf2(uint32_t a, uint32_t b) { uint32_t r; asm("mul.rn.bf16x2 %0, %1, %2;" : "=r"(r) : "r"(a), "r"(b)); return r; }
__device__ __forceinline__ uint32_t fma_bf2(uint32_t a, uint32_t b, uint32_t c) { uint32_t r; asm("fma.rn.bf16x2 %0, %1, %2, %3;" : "=r"(r) : "r"(a), "r"(b), "r"(c)); return r; }
__device__ __forceinline__ float silu(float y) {
  float r; asm("rcp.approx.ftz.f32 %0, %1;" : "=f"(r) : "f"(1.0f + ex2(-1.4426950409f * y)));
  return y * r;
}
__device__ __forceinline__ void stmatrix_x4(uint32_t addr, uint32_t r0, uint32_t r1, uint32_t r2, uint32_t r3) {
  asm volatile("stmatrix.sync.aligned.m8n8.x4.shared.b16 [%0], {%1, %2, %3, %4};" ::"r"(addr), "r"(r0), "r"(r1), "r"(r2), "r"(r3) : "memory");
}
__device__ __forceinline__ void ldmatrix_x4(uint32_t addr, uint32_t& r0, uint32_t& r1, uint32_t& r2, uint32_t& r3) {
  asm volatile("ldmatrix.sync.aligned.m8n8.x4.shared.b16 {%0, %1, %2, %3}, [%4];" : "=r"(r0), "=r"(r1), "=r"(r2), "=r"(r3) : "r"(addr) : "memory");
}

struct Ctx {
  uint32_t sbase;
  uint32_t d16;
  uint32_t rel;
  uint32_t bars;
  uint32_t it;
  uint32_t sc;
  uint32_t stg;
  uint32_t st_off;
  uint32_t st_sw;
  int wg, t;
  int one;
};
__device__ __forceinline__ uint32_t stage_addr(const Ctx& c, uint32_t it) { return c.sbase + (it & 3) * STAGE_BYTES; }
__device__ __forceinline__ void wait_full(const Ctx& c, uint32_t it) { mbar_wait(c.bars + 8 * (it & 3), (it >> 2) & 1); }
__device__ __forceinline__ void release(const Ctx& c, uint32_t it) {
  if (c.t < 2) asm volatile("mbarrier.arrive.shared::cluster.b64 _, [%0];" ::"r"(c.rel + 8 * (it & 3)) : "memory");
}
__device__ __forceinline__ uint64_t desc_of(uint32_t lo) {
  uint64_t d; asm volatile("mov.b64 %0, {%1, %2};" : "=l"(d) : "r"(lo), "r"(0x40000040)); return d;
}
__device__ __forceinline__ uint32_t desc_lo(const Ctx& c, uint32_t addr, uint32_t lbo) { return (addr >> 4) - c.d16 + ((lbo >> 4) << 16); }
template <bool INIT>
__device__ __forceinline__ void mma_step(const Ctx& c, float (&accA)[64], float (&accB)[64], uint32_t it) {
  const uint32_t st = desc_lo(c, c.sbase, 0) + (it & 3) * (STAGE_BYTES >> 4);
  const uint64_t da = desc_of(st + c.wg * 512 + (1 << 16)), db = desc_of(st + 1024 + (512 << 16));
  wgmma_fence();
#pragma unroll
  for (int kk = 0; kk < 4; kk++) wgmma_ss_n256(accA, accB, da + kk * 2, db + kk * 128, (INIT && kk == 0) ? 0 : 1);
  wgmma_commit();
}
__device__ __forceinline__ void stg_acquire(const Ctx& c) { mbar_wait(c.bars + 80 + c.wg * 8, (c.sc & 1) ^ 1); }
__device__ __forceinline__ void stg_commit(Ctx& c) {
  __syncwarp();
  if ((c.t & 31) == 0) mbar_arrive(c.bars + 64 + c.wg * 8);
  c.sc++;
}
template <int OFF>
__device__ __forceinline__ void box_write(const Ctx& c, uint32_t base, const uint32_t (&t)[64]) {
#pragma unroll
  for (int kk = 0; kk < 4; kk++)
    stmatrix_x4(base + c.st_off + (((kk * 2) ^ c.st_sw) << 4), t[OFF + 4 * kk], t[OFF + 4 * kk + 1], t[OFF + 4 * kk + 2], t[OFF + 4 * kk + 3]);
}
__device__ __forceinline__ void acc_write(const Ctx& c, uint32_t base, const float (&s)[64]) {
#pragma unroll
  for (int kk = 0; kk < 8; kk++)
    stmatrix_x4(base + (kk >> 2) * 8192 + c.st_off + ((((kk & 3) * 2) ^ c.st_sw) << 4), pack_bf16(s[8 * kk], s[8 * kk + 1]),
                pack_bf16(s[8 * kk + 2], s[8 * kk + 3]), pack_bf16(s[8 * kk + 4], s[8 * kk + 5]), pack_bf16(s[8 * kk + 6], s[8 * kk + 7]));
}
__device__ __forceinline__ uint32_t opaque(uint32_t v) { asm volatile("" : "+r"(v)); return v; }
__device__ __forceinline__ void half_store(Ctx& c, uint32_t (&t)[64]) {
  stg_acquire(c);
  const uint32_t stg = opaque(c.stg);
  box_write<0>(c, stg, t);
  box_write<16>(c, stg + 8192, t);
  fence_async_smem();
  stg_commit(c);
#pragma unroll
  for (int i = 0; i < 32; i++) asm volatile("mov.b32 %0, %1;" : "=r"(t[i]) : "r"(t[i + 32]));
}
__device__ __forceinline__ void final_half(const Ctx& c, const float (&acc)[64], uint32_t a, uint32_t pitch, const CUtensorMap* m, int col, int row) {
  uint32_t g[32];
#pragma unroll
  for (int kk = 0; kk < 8; kk++)
    ldmatrix_x4(a + (kk >> 2) * pitch + c.st_off + ((((kk & 3) * 2) ^ c.st_sw) << 4), g[4 * kk], g[4 * kk + 1], g[4 * kk + 2], g[4 * kk + 3]);
#pragma unroll
  for (int i = 0; i < 32; i++) g[i] = pack_bf16(acc[2 * i] * bf_lo(g[i]), acc[2 * i + 1] * bf_hi(g[i]));
#pragma unroll
  for (int kk = 0; kk < 8; kk++)
    stmatrix_x4(a + (kk >> 2) * pitch + c.st_off + ((((kk & 3) * 2) ^ c.st_sw) << 4), g[4 * kk], g[4 * kk + 1], g[4 * kk + 2], g[4 * kk + 3]);
  fence_async_smem();
  bar_sync(3 + c.wg, 128);
  if (c.t == 0) {
    fence_async();
    asm volatile("cp.reduce.async.bulk.tensor.2d.global.shared::cta.add.bulk_group [%0, {%2, %3}], [%1];" ::"l"(m), "r"(a), "r"(col), "r"(row) : "memory");
    asm volatile("cp.reduce.async.bulk.tensor.2d.global.shared::cta.add.bulk_group [%0, {%2, %3}], [%1];" ::"l"(m), "r"(a + pitch), "r"(col + 64), "r"(row) : "memory");
    asm volatile("cp.async.bulk.commit_group;" ::: "memory");
  }
}
__device__ __forceinline__ void rotate16(uint32_t (&t)[64]) {
#pragma unroll
  for (int i = 0; i < 16; i++)
    asm volatile("{\n.reg .b32 v;\nmov.b32 v, %0;\nmov.b32 %0, %1;\nmov.b32 %1, %2;\nmov.b32 %2, %3;\nmov.b32 %3, v;\n}\n"
                 : "+r"(t[i]), "+r"(t[i + 16]), "+r"(t[i + 32]), "+r"(t[i + 48]));
}
__device__ __forceinline__ float quad_rcp_sum(float l) {
  l += __shfl_xor_sync(0xffffffffu, l, 1);
  l += __shfl_xor_sync(0xffffffffu, l, 2);
  float r; asm("rcp.approx.ftz.f32 %0, %1;" : "=f"(r) : "f"(l));
  return r;
}
template <int OFF>
__device__ __forceinline__ void capture_plain(uint32_t (&d)[64], const float (&s)[64]) {
#pragma unroll
  for (int i = 0; i < 32; i++) d[OFF + i] = pack_bf16(s[2 * i], s[2 * i + 1]);
}
template <int OFF>
__device__ __forceinline__ void capture_scaled(uint32_t (&d)[64], const float (&s)[64], float r0, float r1) {
#pragma unroll
  for (int i = 0; i < 32; i++) { const float r = (i & 1) ? r1 : r0; d[OFF + i] = pack_bf16(s[2 * i] * r, s[2 * i + 1] * r); }
}
template <int OFF>
__device__ __forceinline__ void capture_gate(uint32_t (&d)[64], const float (&s)[64], float b0, float b1) {
#pragma unroll
  for (int i = 0; i < 32; i++) {
    const float b = (i & 1) ? b1 : b0;
    d[OFF + i] = mul_bf2(pack_bf16(fmaf(s[2 * i], 0.5f, b), fmaf(s[2 * i + 1], 0.5f, b)), d[OFF + i]);
  }
}
template <int K0, int K1>
__device__ __forceinline__ void issue_qk(const Ctx& c, float (&s)[64], uint32_t qaddr, uint32_t it, int z = 0) {
  const uint64_t da = desc_of(desc_lo(c, qaddr, 16) + z), db = desc_of(desc_lo(c, c.sbase, 16) + (it & 3) * (STAGE_BYTES >> 4) + z);
  wgmma_fence();
#pragma unroll
  for (int kk = K0; kk < K1; kk++) wgmma_ss_n128<0>(s, da + (kk >> 2) * 512 + (kk & 3) * 2, db + (kk >> 2) * 1024 + (kk & 3) * 2, kk == 0 ? 0 : 1);
  wgmma_commit();
}
template <int K0, int K1>
__device__ __forceinline__ void issue_pv(const Ctx& c, float (&o)[64], uint32_t paddr, uint32_t it, int first_scale, int z = 0) {
  const uint64_t da = desc_of(desc_lo(c, paddr, 16) + z), db = desc_of(desc_lo(c, c.sbase, 16384) + (it & 3) * (STAGE_BYTES >> 4) + z);
  wgmma_fence();
#pragma unroll
  for (int kk = K0; kk < K1; kk++) wgmma_ss_n128<1>(o, da + (kk >> 2) * 512 + (kk & 3) * 2, db + kk * 128, kk == 0 ? first_scale : 1);
  wgmma_commit();
}
constexpr float SM_SCALE = 0.08838834764831845f * 1.4426950408889634f;
__device__ __forceinline__ void row_max(const float (&s)[64], int t0, int t1, float& x0, float& x1) {
  t0 = max(t0, __shfl_xor_sync(0xffffffffu, t0, 1)); t1 = max(t1, __shfl_xor_sync(0xffffffffu, t1, 1));
  t0 = max(t0, __shfl_xor_sync(0xffffffffu, t0, 2)); t1 = max(t1, __shfl_xor_sync(0xffffffffu, t1, 2));
  if (__builtin_expect(__any_sync(0xffffffffu, t0 == 0 || t1 == 0), 0)) {
    uint32_t u0 = 0xffffffffu, u1 = 0xffffffffu;
#pragma unroll
    for (int i = 0; i < 64; i += 4) {
      u0 = __vimin3_u32(u0, __float_as_uint(s[i]), __float_as_uint(s[i + 1]));
      u1 = __vimin3_u32(u1, __float_as_uint(s[i + 2]), __float_as_uint(s[i + 3]));
    }
    u0 = min(u0, __shfl_xor_sync(0xffffffffu, u0, 1)); u1 = min(u1, __shfl_xor_sync(0xffffffffu, u1, 1));
    u0 = min(u0, __shfl_xor_sync(0xffffffffu, u0, 2)); u1 = min(u1, __shfl_xor_sync(0xffffffffu, u1, 2));
    if (t0 == 0) t0 = (int)u0;
    if (t1 == 0) t1 = (int)u1;
  }
  x0 = __int_as_float(t0); x1 = __int_as_float(t1);
}
struct Att {
  float n0, n1, l0, l1, r0, r1;
  uint32_t it, pb, qb;
  bool rescale, landed;
};
template <int K0, int K1, int C0, int C1>
__device__ __forceinline__ void prob_part(const float (&s)[64], Att& a, const float (&sn)[64], int (&top)[2], uint32_t (&pk)[32]) {
#pragma unroll
  for (int kk = K0; kk < K1; kk++) {
    float e[8];
#pragma unroll
    for (int i = 0; i < 8; i++) asm volatile("ex2.approx.ftz.f32 %0, %1;" : "=f"(e[i]) : "f"(fmaf(s[8 * kk + i], SM_SCALE, (i & 2) ? a.n1 : a.n0)));
    a.l0 += (e[0] + e[1]) + (e[4] + e[5]);
    a.l1 += (e[2] + e[3]) + (e[6] + e[7]);
#pragma unroll
    for (int i = 0; i < 4; i++) asm volatile("cvt.rn.bf16x2.f32 %0, %1, %2;" : "=r"(pk[4 * kk + i]) : "f"(e[2 * i + 1]), "f"(e[2 * i]));
  }
#pragma unroll
  for (int i = 8 * C0; i < 8 * C1; i += 2)
    top[(i >> 1) & 1] = __vimax3_s32(top[(i >> 1) & 1], __float_as_int(sn[i]), __float_as_int(sn[i + 1]));
  asm volatile("" : "+f"(a.l0), "+f"(a.l1), "+r"(top[0]), "+r"(top[1]));
}
constexpr int AS1 = 2, AS2 = 7;
#define RARE(cond) __builtin_expect(!!(cond), 0)
#define ONCE(body) { int rep_ = 0; _Pragma("unroll 1") do { body; } while (++rep_ < c.one); }
template <int MODE, bool ODD>
__device__ __forceinline__ void att_step(Ctx& c, Att& a, int j, float (&s)[64], float (&sn)[64], float (&o)[64]) {
  int top[2] = {0, 0};
  uint32_t pk[32];
  const uint32_t itk = a.it + 1, itv = a.it + (MODE == 1 ? 2 : 1);
  a.it = itv;
  if (MODE != 0) {
    if (RARE(!a.landed)) {
      if (MODE == 1) wait_full(c, itk);
      wait_full(c, itv);
    }
    fence_async_smem();
    if (MODE == 1 && ODD && RARE(j == 5)) stg_commit(c);
    if (MODE == 1 && !ODD && RARE(j == 6)) stg_acquire(c);
    bar_sync(1 + c.wg, 256);
    if (MODE == 1) ONCE((issue_qk<0, 8>(c, sn, j < 3 ? c.stg : a.qb, itk, rep_)))
    else ONCE((issue_pv<0, 8>(c, o, a.pb, itv, 1, rep_), bar_arrive(2 - c.wg, 256)));
  }
  prob_part<0, AS1, 0, 0>(s, a, sn, top, pk);
  if (MODE == 1) ONCE((issue_pv<0, 8>(c, o, a.pb, itv, (j - 1) & 3, rep_), bar_arrive(2 - c.wg, 256)));
  if (MODE == 1) wgmma_wait<1>();
  if (MODE == 0) ONCE(wgmma_wait<0>());
  if (MODE != 2) release(c, itk);
  prob_part<AS1, AS2, 0, MODE != 2 ? 8 : 0>(s, a, sn, top, pk);
  if (MODE != 0) ONCE(wgmma_wait<0>());
  if (MODE != 0) release(c, itv);
  if (MODE == 0) wait_full(c, itv + 1 + c.wg);
  if (MODE == 1 && !ODD) a.pb = j == 6 ? c.stg : a.pb;
#pragma unroll
  for (int kk = 0; kk < AS2; kk++)
    stmatrix_x4(a.pb + (kk >> 2) * 8192 + c.st_off + ((((kk & 3) * 2) ^ c.st_sw) << 4), pk[4 * kk], pk[4 * kk + 1], pk[4 * kk + 2], pk[4 * kk + 3]);
  if (MODE != 2) a.landed = mbar_test2(c.bars + 8 * ((itv + 1) & 3), ((itv + 1) >> 2) & 1, c.bars + 8 * ((itv + 2) & 3), ((itv + 2) >> 2) & 1);
  prob_part<AS2, 8, 0, 0>(s, a, sn, top, pk);
#pragma unroll
  for (int kk = AS2; kk < 8; kk++)
    stmatrix_x4(a.pb + (kk >> 2) * 8192 + c.st_off + ((((kk & 3) * 2) ^ c.st_sw) << 4), pk[4 * kk], pk[4 * kk + 1], pk[4 * kk + 2], pk[4 * kk + 3]);
  const float t0 = (16.f - a.n0) * (1.f / SM_SCALE), t1 = (16.f - a.n1) * (1.f / SM_SCALE);
  const bool over = MODE != 2 && __any_sync(0xffffffffu, top[0] > __float_as_int(t0) || top[1] > __float_as_int(t1));
  const bool renew = MODE != 2 && ((ODD && j == 3) || over);
  if (!RARE(renew || (MODE != 0 && a.rescale))) return;
  if (MODE != 0 && a.rescale) {
#pragma unroll
    for (int i = 0; i < 16; i++) { o[4 * i] *= a.r0; o[4 * i + 1] *= a.r0; o[4 * i + 2] *= a.r1; o[4 * i + 3] *= a.r1; }
    a.rescale = false;
    if (MODE == 1 && !ODD && j == 4) acc_write(c, c.stg, o);
  }
  if (renew) {
    float x0, x1;
    row_max(sn, top[0], top[1], x0, x1);
    x0 *= -SM_SCALE; x1 *= -SM_SCALE;
    if (ODD && j == 3) {
      a.r0 = quad_rcp_sum(a.l0); a.r1 = quad_rcp_sum(a.l1);
      a.l0 = 0.f; a.l1 = 0.f;
    } else {
      x0 = fminf(x0, a.n0); x1 = fminf(x1, a.n1);
      a.r0 = ex2(x0 - a.n0); a.r1 = ex2(x1 - a.n1);
      a.l0 *= a.r0; a.l1 *= a.r1;
    }
    a.n0 = x0; a.n1 = x1;
    a.rescale = true;
  }
}

__device__ __forceinline__ void ln_stats(uint32_t (&t)[64], float& r0, float& b0, float& r1, float& b1, uint32_t zero) {
  float m0 = 0.f, m1 = 0.f;
#pragma unroll
  for (int i = 0; i < 16; i++) { m0 += bf_lo(t[i]) + bf_hi(t[i]); m1 += bf_lo(t[16 + i]) + bf_hi(t[16 + i]); }
#pragma unroll
  for (int o = 16; o > 0; o >>= 1) { m0 += __shfl_xor_sync(0xffffffffu, m0, o); m1 += __shfl_xor_sync(0xffffffffu, m1, o); }
  m0 *= 1.0f / DM; m1 *= 1.0f / DM;
#pragma unroll
  for (int i = 0; i < 32; i++) asm volatile("xor.b32 %0, %0, %1;" : "+r"(t[i]) : "r"(zero));
  float q0 = 0.f, q1 = 0.f;
#pragma unroll
  for (int i = 0; i < 16; i++) {
    const float a = bf_lo(t[i]) - m0, b = bf_hi(t[i]) - m0, c = bf_lo(t[16 + i]) - m1, d = bf_hi(t[16 + i]) - m1;
    q0 = fmaf(a, a, fmaf(b, b, q0)); q1 = fmaf(c, c, fmaf(d, d, q1));
  }
#pragma unroll
  for (int o = 16; o > 0; o >>= 1) { q0 += __shfl_xor_sync(0xffffffffu, q0, o); q1 += __shfl_xor_sync(0xffffffffu, q1, o); }
  r0 = rsqrtf(q0 * (1.0f / DM) + 1e-5f); b0 = -m0 * r0;
  r1 = rsqrtf(q1 * (1.0f / DM) + 1e-5f); b1 = -m1 * r1;
}
__device__ __forceinline__ uint32_t ln_apply(uint32_t w, float r, float b) { return pack_bf16(fmaf(bf_lo(w), r, b), fmaf(bf_hi(w), r, b)); }
__device__ __forceinline__ void ln_fixup(float (&acc)[64], uint32_t csum, float r0, float b0, float r1, float b1) {
#pragma unroll
  for (int j = 0; j < 16; j++) {
    float c0, c1;
    asm volatile("ld.shared.v2.f32 {%0, %1}, [%2];" : "=f"(c0), "=f"(c1) : "r"(csum + j * 32) : "memory");
    acc[4 * j] = fmaf(acc[4 * j], r0, b0 * c0); acc[4 * j + 1] = fmaf(acc[4 * j + 1], r0, b0 * c1);
    acc[4 * j + 2] = fmaf(acc[4 * j + 2], r1, b1 * c0); acc[4 * j + 3] = fmaf(acc[4 * j + 3], r1, b1 * c1);
  }
}

__device__ __forceinline__ unsigned long long tag_pack(float u, float v, uint32_t tag) {
  return ((unsigned long long)((__float_as_uint(u) + 128) >> 8) << 40) | ((unsigned long long)((__float_as_uint(v) + 128) >> 8) << 16) | tag;
}
__device__ __forceinline__ float4 tag_gather(const ulonglong2* src, int stride, int n, uint32_t tag) {
  float4 a = make_float4(0.f, 0.f, 0.f, 0.f);
  uint32_t spins = 0;
#pragma unroll 1
  for (int r = 0; r < n;) {
    unsigned long long u[8];
#pragma unroll
    for (int i = 0; i < 4; i++) {
      u[2 * i] = u[2 * i + 1] = tag;
      if (r + i < n) asm volatile("ld.relaxed.gpu.global.v2.u64 {%0, %1}, [%2];" : "=l"(u[2 * i]), "=l"(u[2 * i + 1]) : "l"(src + (r + i) * stride) : "memory");
    }
    bool ok = true;
#pragma unroll
    for (int i = 0; i < 8; i++) ok = ok && ((uint32_t)u[i] & 0xffffu) == tag;
    if (__all_sync(0xffffffffu, ok)) {
#pragma unroll
      for (int i = 0; i < 4; i++) {
        a.x += __uint_as_float((uint32_t)(u[2 * i] >> 32) & 0xffffff00u); a.y += __uint_as_float((uint32_t)(u[2 * i] >> 8) & 0xffffff00u);
        a.z += __uint_as_float((uint32_t)(u[2 * i + 1] >> 32) & 0xffffff00u); a.w += __uint_as_float((uint32_t)(u[2 * i + 1] >> 8) & 0xffffff00u);
      }
      r += 4;
    } else if (++spins > (1u << 22)) __trap();
  }
  return a;
}

struct Prod {
  uint32_t sbase, bars, it, rank, lane;
};
__device__ __forceinline__ uint32_t prod_acquire(Prod& p, uint32_t bytes) {
  uint32_t s = p.it & 3;
  mbar_wait_idle(p.bars + 32 + 8 * s, ((p.it >> 2) & 1) ^ 1);
  if (p.lane == 0) mbar_expect_tx(p.bars + 8 * s, bytes);
  p.it++;
  return s;
}
__device__ __forceinline__ void dep_wait(const Prod& p, uint32_t& ready, int base, int n, uint32_t target, int i) {
  if ((ready >> i) & 1) return;
  target *= launch_epoch();
  uint32_t spins = 0;
  do {
    const bool ok = (int)p.lane < n && (int)(ld_relaxed(&g_flags[base + p.lane]) - target) >= 0;
    ready = __ballot_sync(0xffffffffu, ok);
    if (++spins > (1u << 22)) __trap();
  } while (!((ready >> i) & 1));
  fence_acquire();
  __syncwarp();
  fence_async();
}
__device__ __forceinline__ void prod_gemm(Prod& p, const CUtensorMap* mA, int arow, const CUtensorMap* mB, int chunk, int k0, int k1,
                                          int base, int n, uint32_t target, int shift, uint32_t& ready) {
#pragma unroll 1
  for (int k = k0; k < k1; k++) {
    dep_wait(p, ready, base, n, target, k >> shift);
    uint32_t s = prod_acquire(p, STAGE_BYTES);
    uint32_t a = p.sbase + s * STAGE_BYTES;
    if (p.lane == 0) {
      tma_load_3d_mc(a + 16384 + p.rank * 16384, mB, p.bars + 8 * s, k * 64, chunk + p.rank * 2);
      tma_load_2d(a, mA, p.bars + 8 * s, k * 64, arow);
    }
  }
}

#define CTA_ROLE                                                   \
  uint32_t cta_;                                                   \
  asm volatile("mov.u32 %0, %%ctaid.x;" : "=r"(cta_));             \
  const int role = ((cta_ >> 1) - (cta_ >> 4)) & 7, mb = (cta_ >> 4) * 2 + (cta_ & 1)

__global__ void __cluster_dims__(2, 1, 1) __launch_bounds__(384, 1) mega_kernel(const __grid_constant__ Params P) {
  extern __shared__ __align__(1024) uint8_t smem_raw[];
  const uint32_t sbase = smem_u32(smem_raw);
  const uint32_t bars = sbase + SM_BAR;
  const int tid = threadIdx.x, lane = tid & 31;
  const int wg = __shfl_sync(0xffffffffu, tid >> 7, 0);
  const uint32_t rank = blockIdx.x & 1;
  if (tid == 256) {
    for (int s = 0; s < STAGES; s++) { mbar_init(bars + 8 * s, 1); mbar_init(bars + 32 + 8 * s, 4); }
    for (int w = 0; w < 2; w++) { mbar_init(bars + 64 + 8 * w, 4); mbar_init(bars + 80 + 8 * w, 1); mbar_init(bars + 96 + 8 * w, 5); mbar_init(bars + 112 + 8 * w, 4); }
    for (int w = 0; w < 2; w++) { mbar_init(bars + 144 + 8 * w, 1); }
    mbar_init(bars + 136, 1);
    mbar_init(bars + 160, 8);
    mbar_init(bars + 168, 3);
    mbar_init(bars + 176, 1);
    mbar_init(bars + 184, 1);
    asm volatile("fence.mbarrier_init.release.cluster;" ::: "memory");
  }

  __syncwarp();
  cluster_arrive_relaxed();

  if (wg == 2) {
    const int warp = __shfl_sync(0xffffffffu, tid >> 5, 0);
    CTA_ROLE;
    if (warp == 9 && lane < M_COUNT) asm volatile("prefetch.tensormap [%0];" ::"l"(&P.maps[lane]) : "memory");
    asm volatile("setmaxnreg.dec.sync.aligned.u32 40;");
    const uint32_t task0 = opaque(P.tasks[role][0]);
    cluster_wait();
    if (warp == 8) {
      Prod p{sbase, bars, 0, rank, (uint32_t)lane};
      {
        const uint32_t task = __shfl_sync(0xffffffffu, task0, 0);
        uint32_t ready = 0xffffffffu;
        prod_gemm(p, &P.maps[M_X], mb * 128, &P.maps[(task & 15) == T_QA ? M_WQ : M_WIN],
                  ((task & 15) == T_Z2 ? FH / 64 : 0) + (task >> 4) * 4, 0, STAGES, 0, 0, 0, 5, ready);
      }
#pragma unroll 1
      for (int ti = 0; ti < MAXT; ti++) {
        const uint32_t task = P.tasks[role][ti];
        const int type = task & 15, idx = task >> 4;
        if (type == T_NONE) break;
        const int arow = mb * 128;
        int mA = M_XN, mB = M_WIN, chunk = idx * 4, nk = 16, base = F_XN + mb, n = 1, shift = 5;
        uint32_t target = 8;
        int k0 = 0;
        if (type == T_Z2) chunk += FH / 64;
        else if (type == T_QA) mB = M_WQ;
        else if (type == T_G) { mA = M_WSP; mB = M_Z2; nk = 32; base = F_Z2N; n = 16; target = 14; shift = 1; }
        else if (type == T_S) { mA = M_O_LD; mB = M_WO; k0 = P.krange[role][0]; nk = P.krange[role][1]; base = F_O + mb * 32; n = 32; target = 2; shift = 1; }
        else if (type == T_Y) { mA = M_H_LD; mB = M_WOUT; nk = 28; base = F_H + mb * 8; n = 7; target = 2; shift = 2; }
        if (ti == 0) { mA = M_X; n = 0; k0 = STAGES; }
        uint32_t ready = n ? 0 : 0xffffffffu;
        prod_gemm(p, &P.maps[mA], arow, &P.maps[mB], chunk, k0, nk, base, n, target, shift, ready);
        if (type == T_QA) {
          const int kvrow = (idx >> 2) * SK + (SK - WIN);
#pragma unroll 1
          for (int j = 0; j < 16; j++) {
            const bool isK = j < 2 || (j < 14 && !(j & 1));
            const int ch = (j < 2 ? j : j >= 14 ? j - 12 : isK ? (j >> 1) + 1 : (j >> 1) - 1) & 3;
            uint32_t s = prod_acquire(p, 32768);
            if (lane == 0) tma_load_2d_mc(sbase + s * STAGE_BYTES + rank * 16384, &P.maps[isK ? M_K : M_V], bars + 8 * s, rank * 64, kvrow + ch * 128);
          }
        }
        if (type == T_S) {
          ready = 0;
          dep_wait(p, ready, F_SY + mb * 4 + idx, 1, 2, 0);
          const uint32_t s = prod_acquire(p, 32768);
          if (lane < 2) tma_load_2d(sbase + s * STAGE_BYTES + lane * 16384, &P.maps[M_SY_LD], bars + 8 * s, idx * 256 + 128 + lane * 64, arow);
        }
      }
    } else if (warp == 9 || warp == 10) {
      const int w = warp - 9;
      {
        const uint32_t task = P.tasks[role][0];
        const int type = task & 15, tile = type == T_Z2 ? task >> 4 : 7;
        const uint32_t slab = sbase + SM_STG + w * 16384;
        const uint32_t tag = launch_epoch() & 0xffffu;
        mbar_wait(bars + 136, 0);
        if (lane == 0) {
          const size_t off = (size_t)(blockIdx.x * 16 + w * 8) * DM;
          mbar_expect_tx(bars + 176 + 8 * w, 16384);
          asm volatile("cp.async.bulk.shared::cluster.global.mbarrier::complete_tx::bytes [%0], [%1], 16384, [%2];" ::"r"(slab), "l"(P.x + off), "r"(bars + 176 + 8 * w) : "memory");
          mbar_wait(bars + 96 + 8 * w, 0);
          fence_async_smem();
          mbar_expect_tx(bars + 176 + 8 * w, 16384);
          tma_load_3d(slab, &P.maps[type == T_QA ? M_WQ : M_WIN], bars + 176 + 8 * w, mb * 64, (type == T_Z2 ? FH / 64 : 0) + (task >> 4) * 4 + w * 2);
        }
        __syncwarp();
        mbar_wait(bars + 176 + 8 * w, 1);
        float4 a = make_float4(0.f, 0.f, 0.f, 0.f);
#pragma unroll 1
        for (int r = 0; r < 64; r += 8) {
          uint32_t v0[8], v1[8];
#pragma unroll
          for (int i = 0; i < 8; i++)
            asm volatile("ld.shared.v2.b32 {%0, %1}, [%2];" : "=r"(v0[i]), "=r"(v1[i]) : "r"(slab + (lane >> 4) * 8192 + (r + i) * 128 + ((((lane & 15) >> 1) ^ i) << 4) + (lane & 1) * 8) : "memory");
#pragma unroll
          for (int i = 0; i < 8; i += 2) {
            a.x += bf_lo(v0[i]) + bf_lo(v0[i + 1]); a.y += bf_hi(v0[i]) + bf_hi(v0[i + 1]);
            a.z += bf_lo(v1[i]) + bf_lo(v1[i + 1]); a.w += bf_hi(v1[i]) + bf_hi(v1[i + 1]);
          }
        }
        asm volatile("st.relaxed.gpu.global.v2.u64 [%0], {%1, %2};" ::"l"(&g_csum[(tile * 16 + mb) * 64 + w * 32 + lane]), "l"(tag_pack(a.x, a.y, tag)), "l"(tag_pack(a.z, a.w, tag)) : "memory");
        a = tag_gather(&g_csum[tile * 16 * 64 + w * 32 + lane], 64, 16, tag);
        asm volatile("st.shared.v4.f32 [%0], {%1, %2, %3, %4};" ::"r"(sbase + SM_CSUM + w * 512 + lane * 16), "f"(a.x), "f"(a.y), "f"(a.z), "f"(a.w) : "memory");
        __syncwarp();
        if (lane == 0) mbar_arrive(bars + 168);
        if (type == T_Z2) {
          mbar_wait_idle(bars + 112 + 8 * w, 0);
          a = tag_gather(reinterpret_cast<const ulonglong2*>(&g_stats[mb * 128 + w * 64 + lane * 2]), SEQ / 2, 7, tag);
          const float m0 = a.x * (1.0f / FH), m1 = a.z * (1.0f / FH);
          const float q0 = rsqrtf(fmaxf(fmaf(-m0, m0, a.y * (1.0f / FH)), 0.f) + 4e-5f);
          const float q1 = rsqrtf(fmaxf(fmaf(-m1, m1, a.w * (1.0f / FH)), 0.f) + 4e-5f);
          asm volatile("st.shared.v4.b32 [%0], {%1, %2, %3, %4};" ::"r"(sbase + SM_STAT + w * 512 + lane * 16), "r"(pack_bf16(q0, q0)), "r"(pack_bf16(-m0 * q0, -m0 * q0)),
                       "r"(pack_bf16(q1, q1)), "r"(pack_bf16(-m1 * q1, -m1 * q1)) : "memory");
          __syncwarp();
          if (lane == 0) mbar_arrive(bars + 144 + 8 * w);
        }
      }
      if (lane == 0) {
        uint32_t sc = 0;
#pragma unroll 1
        for (int ti = 0; ti < MAXT; ti++) {
          const uint32_t task = P.tasks[role][ti];
          const int type = task & 15, idx = task >> 4;
          if (type == T_NONE) break;
          if (type == T_S) {
            flag_wait(F_SY + mb * 4 + idx, 2);
            fence_async();
            mbar_expect_tx(bars + 176 + 8 * w, 16384);
            tma_load_2d(sbase + SM_STG + w * 16384, &P.maps[M_SY_ST], bars + 176 + 8 * w, idx * 256, mb * 128 + w * 64);
            tma_load_2d(sbase + SM_STG + w * 16384 + 8192, &P.maps[M_SY_ST], bars + 176 + 8 * w, idx * 256 + 64, mb * 128 + w * 64);
            const bf16* po = P.out + (size_t)(mb * 128 + w * 64) * DM + idx * 256;
#pragma unroll 1
            for (int q = 0; q < 64; q++, po += DM)
              asm volatile("prefetch.global.L2 [%0];\nprefetch.global.L2 [%0 + 128];\nprefetch.global.L2 [%0 + 256];\nprefetch.global.L2 [%0 + 384];" ::"l"(po));
          }
          if (type == T_Z1 || type == T_S) continue;
          const int mi = type == T_Z2 ? M_Z2_ST : type == T_QA ? M_O_ST : type == T_G ? M_H_ST : M_SY_ST;
          const int f = type == T_Z2 ? F_Z2N + mb : type == T_QA ? F_O + mb * 32 + idx * 2 : type == T_G ? F_H + mb * 8 + idx : F_SY + mb * 4 + idx;
#pragma unroll 1
          for (int q = 0; q < 2; q++, sc++) {
            mbar_wait_idle(bars + 64 + w * 8, sc & 1);
            tma_store_2d(&P.maps[mi], sbase + SM_STG + w * 16384, idx * 256 + q * 128, mb * 128 + w * 64);
            tma_store_2d(&P.maps[mi], sbase + SM_STG + w * 16384 + 8192, idx * 256 + q * 128 + 64, mb * 128 + w * 64);
            asm volatile("cp.async.bulk.commit_group;" ::: "memory");
            asm volatile("cp.async.bulk.wait_group.read 0;" ::: "memory");
            mbar_arrive(bars + 80 + w * 8);
            if (q == 1 || type == T_QA) {
              asm volatile("cp.async.bulk.wait_group 0;" ::: "memory");
              red_release(&g_flags[f + (type == T_QA ? q : 0)]);
            }
          }
        }
      }
    } else {
      {
        {
          mbar_wait(bars + 136, 0);
          const size_t off = ((size_t)(blockIdx.x >> 5) * SK + (SK - WIN) + (blockIdx.x & 31) * 16) * 128 + lane * 64;
          asm volatile("prefetch.global.L2 [%0];" ::"l"(P.kv[0] + off));
          asm volatile("prefetch.global.L2 [%0];" ::"l"(P.kv[1] + off));
        }
        if (lane == 0) {
          mbar_wait(bars + 176, 0);
          mbar_wait(bars + 184, 0);
          asm volatile("cp.async.bulk.global.shared::cta.bulk_group [%0], [%1], 32768;" ::"l"(P.out + (size_t)blockIdx.x * 16 * DM), "r"(sbase + SM_STG) : "memory");
          asm volatile("cp.async.bulk.commit_group;" ::: "memory");
          asm volatile("cp.async.bulk.wait_group.read 0;" ::: "memory");
          mbar_arrive(bars + 96);
          mbar_arrive(bars + 104);
          asm volatile("cp.async.bulk.wait_group 0;" ::: "memory");
        }
        __syncwarp();
        mbar_wait(bars + 160, 0);
        if (lane == 0) red_release(&g_flags[F_XN + (blockIdx.x >> 3)]);
        __syncwarp();
        if (lane == 0) asm volatile("st.shared.u32 [%0], %1;" ::"r"(bars + 128), "r"(launch_epoch()) : "memory");
        flag_wait(F_XN + mb, 8);
        const float4 u0 = __ldcg(reinterpret_cast<const float4*>(&g_xstat[mb * 128]) + lane);
        const float4 u1 = __ldcg(reinterpret_cast<const float4*>(&g_xstat[mb * 128 + 64]) + lane);
        asm volatile("st.shared.v4.f32 [%0], {%1, %2, %3, %4};" ::"r"(sbase + SM_STAT + lane * 16), "f"(u0.x), "f"(u0.y), "f"(u0.z), "f"(u0.w) : "memory");
        asm volatile("st.shared.v4.f32 [%0], {%1, %2, %3, %4};" ::"r"(sbase + SM_STAT + 512 + lane * 16), "f"(u1.x), "f"(u1.y), "f"(u1.z), "f"(u1.w) : "memory");
        __syncwarp();
        if (lane == 0) mbar_arrive(bars + 168);
      }
    }
  } else {
    asm volatile("setmaxnreg.inc.sync.aligned.u32 232;");
    const int warp = tid >> 5;
    CTA_ROLE;
    uint32_t t[64];
#pragma unroll
    for (int i = 0; i < 64; i++) t[i] = 0;
    cluster_wait();
    Ctx c;
    c.sbase = sbase; c.bars = bars; c.it = 0; c.sc = 0; c.wg = wg; c.t = tid & 127; c.one = P.one;
    c.d16 = (sbase & ~0x3FFFFu) >> 4;
    asm volatile("mapa.shared::cluster.u32 %0, %1, %2;" : "=r"(c.rel) : "r"(bars + 32), "r"(tid & 1));
    c.stg = sbase + SM_STG + wg * 16384;
    {
      const int row = (warp & 3) * 16 + ((lane >> 3) & 1) * 8 + (lane & 7);
      c.st_off = row * 128;
      c.st_sw = (lane >> 4) ^ (lane & 7);
    }
    if (wg == 1) bar_arrive(1, 256);
    float accA[64], accB[64];
    int pend = 2, ptype = T_NONE;
    float s0 = 0.f, s1 = 0.f, q0 = 0.f, q1 = 0.f;
    wait_full(c, 0);
    if (tid == 0) mbar_arrive(bars + 136);
    mma_step<true>(c, accA, accB, 0);
#pragma unroll 1
    for (int ti = 0;; ti++) {
      const uint32_t task = P.tasks[role][ti];
      const int type = task & 15;
      const bool is_qa = type == T_QA;
      uint32_t it = c.it + 1;
      const uint32_t nk = type == T_G ? 32 : type == T_Y ? 28 : (type == T_S) ? P.krange[role][1] - P.krange[role][0] : 16;
      const uint32_t last = c.it + nk - 1;
      const uint32_t period = type == T_G ? 4 : (ti == 0 || (ptype == T_Y && nk >= 22)) ? 3 : 2;
      const bool raw = ti == 0;
      uint32_t slot = it + (wg ? period >> 1 : 0) + (raw ? LN_DELAY : 0);
#pragma unroll 1
      for (; it < last; it++) {
        wait_full(c, it);
        mma_step<false>(c, accA, accB, it);
        wgmma_wait<1>();
        release(c, it - 1);
        if (it == slot) {
          const uint32_t stat = sbase + SM_STAT + (wg * 64 + (warp & 3) * 16 + (lane >> 2)) * 8;
          slot += period;
          if (pend > 2) {
            if (ptype == T_Y) {
#pragma unroll
              for (int i = 0; i < 16; i++) t[i] = pack_bf16(silu(bf_lo(t[i])), silu(bf_hi(t[i])));
            } else {
#pragma unroll
              for (int i = 0; i < 16; i++) {
                const float a = gelu2_tanh(bf_lo(t[i])), b = gelu2_tanh(bf_hi(t[i]));
                t[i] = pack_bf16(a, b);
                if (i & 1) { s1 += a + b; q1 = fmaf(a, a, fmaf(b, b, q1)); }
                else { s0 += a + b; q0 = fmaf(a, a, fmaf(b, b, q0)); }
              }
            }
            rotate16(t);
            if (pend == 3) {
              if (ptype == T_Z1) {
                const bf16* bp = P.b_sp + mb * 128 + wg * 64 + (warp & 3) * 16 + (lane >> 2);
                s0 = 0.5f * __bfloat162float(bp[0]); s1 = 0.5f * __bfloat162float(bp[8]);
                pend = 1;
              } else if (ptype == T_Z2) {
                slot += period;
#pragma unroll
                for (int o = 1; o < 4; o <<= 1) {
                  s0 += __shfl_xor_sync(0xffffffffu, s0, o); q0 += __shfl_xor_sync(0xffffffffu, q0, o);
                  s1 += __shfl_xor_sync(0xffffffffu, s1, o); q1 += __shfl_xor_sync(0xffffffffu, q1, o);
                }
                if ((lane & 3) < 2) {
                  const uint32_t t0 = P.tasks[role][0];
                  const int row = mb * 128 + wg * 64 + (warp & 3) * 16 + (lane >> 2) + (lane & 1) * 8;
                  uint32_t epoch;
                  asm volatile("ld.shared.u32 %0, [%1];" : "=r"(epoch) : "r"(bars + 128) : "memory");
                  asm volatile("st.relaxed.gpu.global.u64 [%0], %1;" ::"l"(&g_stats[(t0 >> 4) * SEQ + row]),
                               "l"(tag_pack((lane & 1) ? s1 : s0, (lane & 1) ? q1 : q0, epoch & 0xffffu)) : "memory");
                }
                __syncwarp();
                if (lane == 0) mbar_arrive(bars + 112 + 8 * wg);
              }
            }
          } else if (ptype == T_NONE) {
            if (pend == 2) {
              mbar_wait(bars + 176 + 8 * wg, 0);
#pragma unroll
              for (int i = 0; i < 8; i++)
                asm volatile("ld.shared.v4.u32 {%0, %1, %2, %3}, [%4];" : "=r"(t[4 * i]), "=r"(t[4 * i + 1]), "=r"(t[4 * i + 2]), "=r"(t[4 * i + 3]) : "r"(c.stg + (warp & 3) * 4096 + i * 512 + lane * 16) : "memory");
              __syncwarp();
              if (lane == 0) mbar_arrive(bars + 96 + 8 * wg);
              ln_stats(t, s0, q0, s1, q1, t[32]);
            }
            if (pend == 1) {
              const int row = blockIdx.x * 16 + warp * 2;
              uint4* xo = reinterpret_cast<uint4*>(g_xn + (size_t)row * DM);
#pragma unroll
              for (int i = 0; i < 8; i++) {
                const float r = i < 4 ? s0 : s1, b = i < 4 ? q0 : q1;
                xo[i * 32 + lane] = make_uint4(ln_apply(t[4 * i], r, b), ln_apply(t[4 * i + 1], r, b), ln_apply(t[4 * i + 2], r, b), ln_apply(t[4 * i + 3], r, b));
              }
              if (lane == 0) *reinterpret_cast<float4*>(&g_xstat[row]) = make_float4(s0, q0, s1, q1);
              __syncwarp();
              if (lane == 0) mbar_arrive(bars + 160);
            }
          } else {
            if (ptype == T_Z2) {
              uint32_t a0, b0, a1, b1;
              mbar_wait(bars + 144 + 8 * wg, 0);
              asm volatile("ld.shared.v2.b32 {%0, %1}, [%2];" : "=r"(a0), "=r"(b0) : "r"(stat) : "memory");
              asm volatile("ld.shared.v2.b32 {%0, %1}, [%2];" : "=r"(a1), "=r"(b1) : "r"(stat + 64) : "memory");
#pragma unroll
              for (int i = 0; i < 32; i++) t[i] = fma_bf2(t[i], (i & 1) ? a1 : a0, (i & 1) ? b1 : b0);
            }
            half_store(c, t);
          }
          if (--pend == 0) slot = last;
        }
      }
      wait_full(c, it);
      if (is_qa) stg_acquire(c);
      bar_sync(1 + wg, 256);
      mma_step<false>(c, accA, accB, it);
      bar_arrive(2 - wg, 256);
      wgmma_wait<1>();
      release(c, it - 1);
      wgmma_wait<0>();
      release(c, it);
      it++;
      if (type == T_S) {
        const int col = (task >> 4) * 256, row = mb * 128 + wg * 64;
        mbar_wait(bars + 176 + 8 * wg, 0);
#pragma unroll 1
        for (int h = 0;; h++) {
          final_half(c, accA, h ? stage_addr(c, it) + wg * 8192 : c.stg, h ? 16384 : 8192, &P.maps[M_OUT], col + h * 128, row);
          if (h) break;
#pragma unroll
          for (int i = 0; i < 64; i++) accA[i] = accB[i];
          wait_full(c, it);
        }
        if (c.t == 0) asm volatile("cp.async.bulk.wait_group.read 0;" ::: "memory");
        break;
      }
      if (raw) {
        const uint32_t stat = sbase + SM_STAT + (wg * 64 + (warp & 3) * 16 + (lane >> 2)) * 8;
        mbar_wait(bars + 168, 0);
        asm volatile("ld.shared.v2.f32 {%0, %1}, [%2];" : "=f"(s0), "=f"(q0) : "r"(stat) : "memory");
        asm volatile("ld.shared.v2.f32 {%0, %1}, [%2];" : "=f"(s1), "=f"(q1) : "r"(stat + 64) : "memory");
        ln_fixup(accA, sbase + SM_CSUM + (lane & 3) * 8, s0, q0, s1, q1);
        ln_fixup(accB, sbase + SM_CSUM + 512 + (lane & 3) * 8, s0, q0, s1, q1);
      }
      if (is_qa) {
        acc_write(c, opaque(c.stg), accA);
        Att a;
        a.qb = stage_addr(c, it + wg) + 32768;
        a.pb = stage_addr(c, it + 2 + wg) + 32768;
        float sa[64], sb[64], o[64];
#pragma unroll
        for (int i = 0; i < 64; i++) { sa[i] = 0.f; sb[i] = 0.f; }
        wait_full(c, it);
        wait_full(c, it + 1);
        fence_async_smem();
        bar_sync(1 + wg, 256);
        issue_qk<0, 8>(c, sa, c.stg, it);
        acc_write(c, a.qb, accB);
        issue_qk<0, 8>(c, sb, c.stg, it + 1);
        bar_arrive(2 - wg, 256);
        wgmma_wait<1>();
        release(c, it);
        a.it = it; a.l0 = 0.f; a.l1 = 0.f; a.r0 = 0.f; a.r1 = 0.f; a.rescale = false;
        {
          float x0, x1;
          int m[4] = {0, 0, 0, 0};
#pragma unroll
          for (int i = 0; i < 64; i += 2) m[(i >> 1) & 3] = __vimax3_s32(m[(i >> 1) & 3], __float_as_int(sa[i]), __float_as_int(sa[i + 1]));
          row_max(sa, max(m[0], m[2]), max(m[1], m[3]), x0, x1);
          a.n0 = -x0 * SM_SCALE; a.n1 = -x1 * SM_SCALE;
        }
        att_step<0, false>(c, a, 0, sa, sb, o);
#pragma unroll
        for (int i = 0; i < 64; i++) o[i] = 0.f;
#pragma unroll 1
        for (int j = 1; j < 7; j += 2) {
          att_step<1, true>(c, a, j, sb, sa, o);
          att_step<1, false>(c, a, j + 1, sa, sb, o);
        }
        att_step<2, true>(c, a, 7, sb, sa, o);
        it = a.it + 1;
        wait_full(c, it);
        fence_async_smem();
        bar_sync(1 + wg, 256);
        issue_pv<0, 8>(c, o, a.pb, it, 1);
        it++;
#pragma unroll
        for (int i = 0; i < 64; i++) { accA[i] = 0.f; accB[i] = 0.f; }
        wait_full(c, it);
        mma_step<true>(c, accA, accB, it);
        bar_arrive(2 - wg, 256);
        const float r0 = quad_rcp_sum(a.l0), r1 = quad_rcp_sum(a.l1);
        wgmma_wait<1>();
        release(c, it - 1);
        capture_scaled<0>(t, o, r0, r1);
#pragma unroll
        for (int i = 32; i < 64; i++) t[i] = 0;
      } else {
        if (type == T_G) {
          capture_gate<0>(t, accA, s0, s1);
          capture_gate<32>(t, accB, s0, s1);
        } else {
          capture_plain<0>(t, accA);
          capture_plain<32>(t, accB);
        }
        wait_full(c, it);
        mma_step<true>(c, accA, accB, it);
      }
      c.it = it;
      s0 = 0.f; s1 = 0.f; q0 = 0.f; q1 = 0.f;
      pend = is_qa ? 1 : (type == T_Z2 || type == T_Z1 || type == T_Y) ? 6 : 2;
      ptype = type;
    }
    wgmma_wait<0>();
  }
  __syncwarp();
  cluster_arrive_relaxed();
  cluster_wait();
  if (tid == 0) asm volatile("red.relaxed.gpu.global.add.u32 [%0], 1;" ::"l"(&g_flags[F_EPOCH + blockIdx.x]) : "memory");
}

typedef CUresult (*PFN_encodeTiled)(CUtensorMap*, CUtensorMapDataType, cuuint32_t, void*, const cuuint64_t*, const cuuint64_t*, const cuuint32_t*,
                                    const cuuint32_t*, CUtensorMapInterleave, CUtensorMapSwizzle, CUtensorMapL2promotion, CUtensorMapFloatOOBfill);

static void map_2d(PFN_encodeTiled enc, CUtensorMap* m, const void* ptr, uint64_t rows, uint64_t cols, uint32_t box_rows = 128) {
  cuuint64_t dims[2] = {cols, rows}; cuuint64_t strides[1] = {cols * 2};
  cuuint32_t box[2] = {64, box_rows}; cuuint32_t es[2] = {1, 1};
  enc(m, CU_TENSOR_MAP_DATA_TYPE_BFLOAT16, 2, const_cast<void*>(ptr), dims, strides, box, es, CU_TENSOR_MAP_INTERLEAVE_NONE,
      CU_TENSOR_MAP_SWIZZLE_128B, CU_TENSOR_MAP_L2_PROMOTION_L2_256B, CU_TENSOR_MAP_FLOAT_OOB_FILL_NONE);
}
static void map_3d(PFN_encodeTiled enc, CUtensorMap* m, const void* ptr, uint64_t rows, uint64_t cols) {
  cuuint64_t dims[3] = {64, rows, cols / 64}; cuuint64_t strides[2] = {cols * 2, 128};
  cuuint32_t box[3] = {64, 64, 2}; cuuint32_t es[3] = {1, 1, 1};
  enc(m, CU_TENSOR_MAP_DATA_TYPE_BFLOAT16, 3, const_cast<void*>(ptr), dims, strides, box, es, CU_TENSOR_MAP_INTERLEAVE_NONE,
      CU_TENSOR_MAP_SWIZZLE_128B, CU_TENSOR_MAP_L2_PROMOTION_L2_256B, CU_TENSOR_MAP_FLOAT_OOB_FILL_NONE);
}
static unsigned char mk(int type, int idx) { return (unsigned char)(type | (idx << 4)); }

static void build_schedule(Params& P) {
  static const char* const plan[8] = {
      "q0 h1 q9 y0 s0:37-64",
      "z0 q1 h2 q12 s0:0-37",
      "z2 q3 q7 q10 y1 s1:40-64",
      "z1 q2 h3 q13 s1:0-40",
      "z4 q5 q8 q11 y2 s2:40-64",
      "z3 q4 h4 q14 s2:0-40",
      "z6 h0 h6 y3 s3:37-64",
      "z5 q6 h5 q15 s3:0-37",
  };
  for (int j = 0; j < 8; j++) {
    unsigned char* T = P.tasks[j];
    int n = 0;
    for (const char* q = plan[j]; *q;) {
      const char kind = *q++;
      int v[3] = {0, 0, 0};
      for (int f = 0; *q && *q != ' '; q++) {
        if (*q == ':' || *q == '-') f++;
        else v[f] = v[f] * 10 + (*q - '0');
      }
      while (*q == ' ') q++;
      if (kind == 'z') T[n++] = mk(T_Z2, v[0]);
      else if (kind == 'q') T[n++] = mk(T_QA, v[0]);
      else if (kind == 'h') { T[n++] = mk(T_Z1, v[0]); T[n++] = mk(T_G, v[0]); }
      else if (kind == 'y') T[n++] = mk(T_Y, v[0]);
      else { T[n++] = mk(T_S, v[0]); P.krange[j][0] = (unsigned char)v[1]; P.krange[j][1] = (unsigned char)v[2]; }
    }
    while (n < MAXT) T[n++] = 0;
  }
}

extern "C" void kernel_launch(void* const* d_in, const int* in_sizes, int n_in, void* d_out, int out_size) {
  (void)in_sizes; (void)n_in; (void)out_size;
  static PFN_encodeTiled enc = nullptr;
  static void *p_xn, *p_z2, *p_o, *p_h, *p_sy;
  if (!enc) {
    void* fn = nullptr; cudaDriverEntryPointQueryResult qr;
    cudaGetDriverEntryPoint("cuTensorMapEncodeTiled", &fn, cudaEnableDefault, &qr);
    enc = (PFN_encodeTiled)fn;
    cudaGetSymbolAddress(&p_xn, g_xn); cudaGetSymbolAddress(&p_z2, g_z2); cudaGetSymbolAddress(&p_o, g_o);
    cudaGetSymbolAddress(&p_h, g_h); cudaGetSymbolAddress(&p_sy, g_sy);
    cudaFuncSetAttribute(mega_kernel, cudaFuncAttributeMaxDynamicSharedMemorySize, SMEM_BYTES);
  }
  Params P;
  map_2d(enc, &P.maps[M_XN], p_xn, SEQ, DM);
  map_2d(enc, &P.maps[M_WSP], d_in[7], SEQ, SEQ);
  map_2d(enc, &P.maps[M_O_LD], p_o, SEQ, HD);
  map_2d(enc, &P.maps[M_H_LD], p_h, SEQ, FH);
  map_2d(enc, &P.maps[M_X], d_in[0], SEQ, DM);
  map_2d(enc, &P.maps[M_SY_LD], p_sy, SEQ, DM);
  map_2d(enc, &P.maps[M_K], d_in[1], 4 * SK, 128);
  map_2d(enc, &P.maps[M_V], d_in[2], 4 * SK, 128);
  map_3d(enc, &P.maps[M_WIN], d_in[6], DM, FF);
  map_3d(enc, &P.maps[M_WQ], d_in[3], DM, HD);
  map_3d(enc, &P.maps[M_Z2], p_z2, SEQ, FH);
  map_3d(enc, &P.maps[M_WO], d_in[4], HD, DM);
  map_3d(enc, &P.maps[M_WOUT], d_in[9], FH, DM);
  map_2d(enc, &P.maps[M_Z2_ST], p_z2, SEQ, FH, 64);
  map_2d(enc, &P.maps[M_O_ST], p_o, SEQ, HD, 64);
  map_2d(enc, &P.maps[M_H_ST], p_h, SEQ, FH, 64);
  map_2d(enc, &P.maps[M_SY_ST], p_sy, SEQ, DM, 64);
  map_2d(enc, &P.maps[M_OUT], d_out, SEQ, DM, 64);
  P.x = (const bf16*)d_in[0];
  P.out = (bf16*)d_out;
  P.b_sp = (const bf16*)d_in[8];
  P.kv[0] = (const bf16*)d_in[1];
  P.kv[1] = (const bf16*)d_in[2];
  P.one = 1;
  build_schedule(P);
  mega_kernel<<<NCLUSTERS * 2, 384, SMEM_BYTES, cudaStreamPerThread>>>(P);
}
```

```cpp
#include <cuda_runtime.h>
#include <cuda_bf16.h>
#include <cuda.h>
#include <stdint.h>

typedef __nv_bfloat16 bf16;

constexpr int SEQ = 2048, DM = 1024, HD = 4096, FF = 3584, FH = 1792, SK = 2048, WIN = 512;
constexpr int NCLUSTERS = 66;
constexpr int MAXT = 8;
constexpr int LN_DELAY = 2;

__device__ __align__(1024) bf16 g_xn[SEQ * DM];
__device__ __align__(1024) bf16 g_z2[SEQ * FH];
__device__ __align__(1024) bf16 g_o[SEQ * HD];
__device__ __align__(1024) bf16 g_h[SEQ * FH];
__device__ __align__(1024) bf16 g_sy[SEQ * DM];
constexpr int F_XN = 0;
constexpr int F_Z2N = 16;
constexpr int F_O = 64;
constexpr int F_H = 576;
constexpr int F_SY = 704;
constexpr int F_EPOCH = 768;
constexpr int F_COUNT = 1024;
__device__ __align__(16) unsigned int g_flags[F_COUNT];
__device__ __align__(16) float2 g_xstat[SEQ];
__device__ ulonglong2 g_csum[8 * 16 * 64];
__device__ __align__(16) unsigned long long g_stats[8 * SEQ];

enum { M_XN = 0, M_WSP, M_O_LD, M_H_LD, M_X, M_SY_LD, M_K, M_V,
       M_WIN, M_WQ, M_Z2, M_WO, M_WOUT,
       M_Z2_ST, M_O_ST, M_H_ST, M_SY_ST, M_OUT,
       M_COUNT };
enum { T_NONE = 0, T_Z2, T_QA, T_Z1, T_G, T_Y, T_S };

struct Params {
  CUtensorMap maps[M_COUNT];
  const bf16* x;
  bf16* out;
  const bf16* b_sp;
  const bf16* kv[2];
  int one;
  unsigned char tasks[9][MAXT];
  unsigned char krange[9][2];
};

constexpr int STAGES = 4;
constexpr int STAGE_BYTES = 49152;
constexpr int SM_STG = STAGES * STAGE_BYTES;
constexpr int SM_BAR = SM_STG + 32768;
constexpr int SM_STAT = SM_BAR + 256;
constexpr int SM_CSUM = SM_STAT + 1024;
constexpr int SMEM_BYTES = SM_CSUM + 1024;

template <int TB>
__device__ __forceinline__ void wgmma_ss_n128(float (&d)[64], uint64_t da, uint64_t db, int scale_d) {
  asm volatile("{\n.reg .pred p;\nsetp.ne.b32 p, %66, 0;\n"
    "wgmma.mma_async.sync.aligned.m64n128k16.f32.bf16.bf16 {%0, %1, %2, %3, %4, %5, %6, %7, %8, %9, %10, %11, %12, %13, %14, %15, %16, %17, %18, %19, %20, %21, %22, %23, %24, %25, %26, %27, %28, %29, %30, %31, %32, %33, %34, %35, %36, %37, %38, %39, %40, %41, %42, %43, %44, %45, %46, %47, %48, %49, %50, %51, %52, %53, %54, %55, %56, %57, %58, %59, %60, %61, %62, %63}, %64, %65, p, 1, 1, 0, %67;\n}\n"
    : "+f"(d[0]), "+f"(d[1]), "+f"(d[2]), "+f"(d[3]), "+f"(d[4]), "+f"(d[5]), "+f"(d[6]), "+f"(d[7]), "+f"(d[8]), "+f"(d[9]), "+f"(d[10]), "+f"(d[11]), "+f"(d[12]), "+f"(d[13]), "+f"(d[14]), "+f"(d[15]), "+f"(d[16]), "+f"(d[17]), "+f"(d[18]), "+f"(d[19]), "+f"(d[20]), "+f"(d[21]), "+f"(d[22]), "+f"(d[23]), "+f"(d[24]), "+f"(d[25]), "+f"(d[26]), "+f"(d[27]), "+f"(d[28]), "+f"(d[29]), "+f"(d[30]), "+f"(d[31]), "+f"(d[32]), "+f"(d[33]), "+f"(d[34]), "+f"(d[35]), "+f"(d[36]), "+f"(d[37]), "+f"(d[38]), "+f"(d[39]), "+f"(d[40]), "+f"(d[41]), "+f"(d[42]), "+f"(d[43]), "+f"(d[44]), "+f"(d[45]), "+f"(d[46]), "+f"(d[47]), "+f"(d[48]), "+f"(d[49]), "+f"(d[50]), "+f"(d[51]), "+f"(d[52]), "+f"(d[53]), "+f"(d[54]), "+f"(d[55]), "+f"(d[56]), "+f"(d[57]), "+f"(d[58]), "+f"(d[59]), "+f"(d[60]), "+f"(d[61]), "+f"(d[62]), "+f"(d[63])
    : "l"(da), "l"(db), "r"(scale_d), "n"(TB));
}
__device__ __forceinline__ void wgmma_ss_n256(float (&d)[64], float (&e)[64], uint64_t da, uint64_t db, int scale_d) {
  asm volatile("{\n.reg .pred p;\nsetp.ne.b32 p, %130, 0;\n"
    "wgmma.mma_async.sync.aligned.m64n256k16.f32.bf16.bf16 {%0, %1, %2, %3, %4, %5, %6, %7, %8, %9, %10, %11, %12, %13, %14, %15, %16, %17, %18, %19, %20, %21, %22, %23, %24, %25, %26, %27, %28, %29, %30, %31, %32, %33, %34, %35, %36, %37, %38, %39, %40, %41, %42, %43, %44, %45, %46, %47, %48, %49, %50, %51, %52, %53, %54, %55, %56, %57, %58, %59, %60, %61, %62, %63, %64, %65, %66, %67, %68, %69, %70, %71, %72, %73, %74, %75, %76, %77, %78, %79, %80, %81, %82, %83, %84, %85, %86, %87, %88, %89, %90, %91, %92, %93, %94, %95, %96, %97, %98, %99, %100, %101, %102, %103, %104, %105, %106, %107, %108, %109, %110, %111, %112, %113, %114, %115, %116, %117, %118, %119, %120, %121, %122, %123, %124, %125, %126, %127}, %128, %129, p, 1, 1, 0, 1;\n}\n"
    : "+f"(d[0]), "+f"(d[1]), "+f"(d[2]), "+f"(d[3]), "+f"(d[4]), "+f"(d[5]), "+f"(d[6]), "+f"(d[7]), "+f"(d[8]), "+f"(d[9]), "+f"(d[10]), "+f"(d[11]), "+f"(d[12]), "+f"(d[13]), "+f"(d[14]), "+f"(d[15]), "+f"(d[16]), "+f"(d[17]), "+f"(d[18]), "+f"(d[19]), "+f"(d[20]), "+f"(d[21]), "+f"(d[22]), "+f"(d[23]), "+f"(d[24]), "+f"(d[25]), "+f"(d[26]), "+f"(d[27]), "+f"(d[28]), "+f"(d[29]), "+f"(d[30]), "+f"(d[31]), "+f"(d[32]), "+f"(d[33]), "+f"(d[34]), "+f"(d[35]), "+f"(d[36]), "+f"(d[37]), "+f"(d[38]), "+f"(d[39]), "+f"(d[40]), "+f"(d[41]), "+f"(d[42]), "+f"(d[43]), "+f"(d[44]), "+f"(d[45]), "+f"(d[46]), "+f"(d[47]), "+f"(d[48]), "+f"(d[49]), "+f"(d[50]), "+f"(d[51]), "+f"(d[52]), "+f"(d[53]), "+f"(d[54]), "+f"(d[55]), "+f"(d[56]), "+f"(d[57]), "+f"(d[58]), "+f"(d[59]), "+f"(d[60]), "+f"(d[61]), "+f"(d[62]), "+f"(d[63]), "+f"(e[0]), "+f"(e[1]), "+f"(e[2]), "+f"(e[3]), "+f"(e[4]), "+f"(e[5]), "+f"(e[6]), "+f"(e[7]), "+f"(e[8]), "+f"(e[9]), "+f"(e[10]), "+f"(e[11]), "+f"(e[12]), "+f"(e[13]), "+f"(e[14]), "+f"(e[15]), "+f"(e[16]), "+f"(e[17]), "+f"(e[18]), "+f"(e[19]), "+f"(e[20]), "+f"(e[21]), "+f"(e[22]), "+f"(e[23]), "+f"(e[24]), "+f"(e[25]), "+f"(e[26]), "+f"(e[27]), "+f"(e[28]), "+f"(e[29]), "+f"(e[30]), "+f"(e[31]), "+f"(e[32]), "+f"(e[33]), "+f"(e[34]), "+f"(e[35]), "+f"(e[36]), "+f"(e[37]), "+f"(e[38]), "+f"(e[39]), "+f"(e[40]), "+f"(e[41]), "+f"(e[42]), "+f"(e[43]), "+f"(e[44]), "+f"(e[45]), "+f"(e[46]), "+f"(e[47]), "+f"(e[48]), "+f"(e[49]), "+f"(e[50]), "+f"(e[51]), "+f"(e[52]), "+f"(e[53]), "+f"(e[54]), "+f"(e[55]), "+f"(e[56]), "+f"(e[57]), "+f"(e[58]), "+f"(e[59]), "+f"(e[60]), "+f"(e[61]), "+f"(e[62]), "+f"(e[63])
    : "l"(da), "l"(db), "r"(scale_d));
}

__device__ __forceinline__ uint32_t smem_u32(const void* p) { return (uint32_t)__cvta_generic_to_shared(p); }
__device__ __forceinline__ void mbar_init(uint32_t bar, uint32_t cnt) { asm volatile("mbarrier.init.shared::cta.b64 [%0], %1;" ::"r"(bar), "r"(cnt) : "memory"); }
__device__ __forceinline__ void mbar_expect_tx(uint32_t bar, uint32_t bytes) { asm volatile("mbarrier.arrive.expect_tx.shared::cta.b64 _, [%0], %1;" ::"r"(bar), "r"(bytes) : "memory"); }
__device__ __forceinline__ void mbar_arrive(uint32_t bar) { asm volatile("mbarrier.arrive.shared::cta.b64 _, [%0];" ::"r"(bar) : "memory"); }
__device__ __forceinline__ void mbar_wait(uint32_t bar, uint32_t parity) {
  asm volatile(
      "{\n.reg .pred p;\n.reg .u32 n;\nmov.u32 n, 0;\n"
      "LAB_WAIT:\nmbarrier.try_wait.parity.shared::cta.b64 p, [%0], %1;\n@p bra LAB_DONE;\n"
      "add.u32 n, n, 1;\nsetp.lt.u32 p, n, 4194304;\n@p bra LAB_WAIT;\ntrap;\nLAB_DONE:\n}\n" ::"r"(bar), "r"(parity) : "memory");
}
__device__ __forceinline__ void mbar_wait_idle(uint32_t bar, uint32_t parity) {
  asm volatile(
      "{\n.reg .pred p;\n.reg .u32 n;\nmov.u32 n, 0;\n"
      "LAB_WAIT:\nmbarrier.try_wait.parity.shared::cta.b64 p, [%0], %1, 1000;\n@p bra LAB_DONE;\n"
      "add.u32 n, n, 1;\nsetp.lt.u32 p, n, 4194304;\n@p bra LAB_WAIT;\ntrap;\nLAB_DONE:\n}\n" ::"r"(bar), "r"(parity) : "memory");
}
__device__ __forceinline__ bool mbar_test2(uint32_t bar0, uint32_t par0, uint32_t bar1, uint32_t par1) {
  uint32_t ok;
  asm volatile("{\n.reg .pred p, q;\nmbarrier.test_wait.parity.shared::cta.b64 p, [%1], %2;\nmbarrier.test_wait.parity.shared::cta.b64 q, [%3], %4;\n"
               "and.pred p, p, q;\nvote.sync.all.pred p, p, 0xffffffff;\nselp.u32 %0, 1, 0, p;\n}\n" : "=r"(ok) : "r"(bar0), "r"(par0), "r"(bar1), "r"(par1) : "memory");
  return ok != 0;
}
__device__ __forceinline__ void tma_load_2d(uint32_t dst, const CUtensorMap* tm, uint32_t bar, int c0, int c1) {
  asm volatile("cp.async.bulk.tensor.2d.shared::cluster.global.mbarrier::complete_tx::bytes [%0], [%1, {%3, %4}], [%2];" ::"r"(dst), "l"(tm), "r"(bar), "r"(c0), "r"(c1) : "memory");
}
__device__ __forceinline__ void tma_load_2d_mc(uint32_t dst, const CUtensorMap* tm, uint32_t bar, int c0, int c1) {
  asm volatile("cp.async.bulk.tensor.2d.shared::cluster.global.mbarrier::complete_tx::bytes.multicast::cluster [%0], [%1, {%3, %4}], [%2], %5;" ::"r"(dst), "l"(tm), "r"(bar), "r"(c0), "r"(c1), "h"((uint16_t)3) : "memory");
}
__device__ __forceinline__ void tma_load_3d_mc(uint32_t dst, const CUtensorMap* tm, uint32_t bar, int row, int chunk) {
  asm volatile("cp.async.bulk.tensor.3d.shared::cluster.global.mbarrier::complete_tx::bytes.multicast::cluster [%0], [%1, {%3, %4, %5}], [%2], %6;" ::"r"(dst), "l"(tm), "r"(bar), "r"(0), "r"(row), "r"(chunk), "h"((uint16_t)3) : "memory");
}
__device__ __forceinline__ void tma_load_3d(uint32_t dst, const CUtensorMap* tm, uint32_t bar, int row, int chunk) {
  asm volatile("cp.async.bulk.tensor.3d.shared::cluster.global.mbarrier::complete_tx::bytes [%0], [%1, {%3, %4, %5}], [%2];" ::"r"(dst), "l"(tm), "r"(bar), "r"(0), "r"(row), "r"(chunk) : "memory");
}
__device__ __forceinline__ void tma_store_2d(const CUtensorMap* tm, uint32_t src, int col, int row) {
  asm volatile("cp.async.bulk.tensor.2d.global.shared::cta.bulk_group [%0, {%2, %3}], [%1];" ::"l"(tm), "r"(src), "r"(col), "r"(row) : "memory");
}
__device__ __forceinline__ void wgmma_fence() { asm volatile("wgmma.fence.sync.aligned;" ::: "memory"); }
__device__ __forceinline__ void wgmma_commit() { asm volatile("wgmma.commit_group.sync.aligned;" ::: "memory"); }
template <int N> __device__ __forceinline__ void wgmma_wait() { asm volatile("wgmma.wait_group.sync.aligned %0;" ::"n"(N) : "memory"); }
__device__ __forceinline__ void fence_async() { asm volatile("fence.proxy.async.global;" ::: "memory"); }
__device__ __forceinline__ void fence_async_smem() { asm volatile("fence.proxy.async.shared::cta;" ::: "memory"); }
__device__ __forceinline__ void cluster_arrive_relaxed() { asm volatile("barrier.cluster.arrive.relaxed;" ::: "memory"); }
__device__ __forceinline__ void cluster_wait() { asm volatile("barrier.cluster.wait.acquire;" ::: "memory"); }
__device__ __forceinline__ void bar_sync(int id, int n) { asm volatile("bar.sync %0, %1;" ::"r"(id), "r"(n) : "memory"); }
__device__ __forceinline__ void bar_arrive(int id, int n) { asm volatile("bar.arrive %0, %1;" ::"r"(id), "r"(n) : "memory"); }
__device__ __forceinline__ uint32_t ld_relaxed(const unsigned int* p) {
  uint32_t v; asm volatile("ld.relaxed.gpu.global.u32 %0, [%1];" : "=r"(v) : "l"(p) : "memory"); return v;
}
__device__ __forceinline__ void fence_acquire() { asm volatile("fence.acquire.gpu;" ::: "memory"); }
__device__ __forceinline__ void red_release(unsigned int* p) { asm volatile("red.release.gpu.global.add.u32 [%0], 1;" ::"l"(p) : "memory"); }
__device__ __forceinline__ uint32_t launch_epoch() { return ld_relaxed(&g_flags[F_EPOCH + blockIdx.x]) + 1; }
__device__ __forceinline__ void flag_wait(int idx, uint32_t target) {
  uint32_t n = 0;
  target *= launch_epoch();
  while ((int)(ld_relaxed(&g_flags[idx]) - target) < 0) {
    __nanosleep(20);
    if (++n > (1u << 22)) __trap();
  }
  fence_acquire();
}
__device__ __forceinline__ uint32_t pack_bf16(float lo, float hi) {
  uint32_t r; asm("cvt.rn.bf16x2.f32 %0, %1, %2;" : "=r"(r) : "f"(hi), "f"(lo)); return r;
}
__device__ __forceinline__ float bf_lo(uint32_t v) { return __uint_as_float(v << 16); }
__device__ __forceinline__ float bf_hi(uint32_t v) { return __uint_as_float(v & 0xffff0000u); }
__device__ __forceinline__ float ex2(float x) { float r; asm("ex2.approx.ftz.f32 %0, %1;" : "=f"(r) : "f"(x)); return r; }
__device__ __forceinline__ float tanh_fast(float x) { float r; asm("tanh.approx.f32 %0, %1;" : "=f"(r) : "f"(x)); return r; }
__device__ __forceinline__ float gelu2_tanh(float x) {
  float u = x * fmaf(x * x, 0.0356774081f, 0.7978845608f);
  return fmaf(x, tanh_fast(u), x);
}
__device__ __forceinline__ uint32_t mul_bf2(uint32_t a, uint32_t b) { uint32_t r; asm("mul.rn.bf16x2 %0, %1, %2;" : "=r"(r) : "r"(a), "r"(b)); return r; }
__device__ __forceinline__ uint32_t fma_bf2(uint32_t a, uint32_t b, uint32_t c) { uint32_t r; asm("fma.rn.bf16x2 %0, %1, %2, %3;" : "=r"(r) : "r"(a), "r"(b), "r"(c)); return r; }
__device__ __forceinline__ float silu(float y) {
  float r; asm("rcp.approx.ftz.f32 %0, %1;" : "=f"(r) : "f"(1.0f + ex2(-1.4426950409f * y)));
  return y * r;
}
__device__ __forceinline__ void stmatrix_x4(uint32_t addr, uint32_t r0, uint32_t r1, uint32_t r2, uint32_t r3) {
  asm volatile("stmatrix.sync.aligned.m8n8.x4.shared.b16 [%0], {%1, %2, %3, %4};" ::"r"(addr), "r"(r0), "r"(r1), "r"(r2), "r"(r3) : "memory");
}
__device__ __forceinline__ void ldmatrix_x4(uint32_t addr, uint32_t& r0, uint32_t& r1, uint32_t& r2, uint32_t& r3) {
  asm volatile("ldmatrix.sync.aligned.m8n8.x4.shared.b16 {%0, %1, %2, %3}, [%4];" : "=r"(r0), "=r"(r1), "=r"(r2), "=r"(r3) : "r"(addr) : "memory");
}

struct Ctx {
  uint32_t sbase;
  uint32_t d16;
  uint32_t rel;
  uint32_t bars;
  uint32_t it;
  uint32_t sc;
  uint32_t stg;
  uint32_t st_off;
  uint32_t st_sw;
  int wg, t;
  int one;
};
__device__ __forceinline__ uint32_t stage_addr(const Ctx& c, uint32_t it) { return c.sbase + (it & 3) * STAGE_BYTES; }
__device__ __forceinline__ void wait_full(const Ctx& c, uint32_t it) { mbar_wait(c.bars + 8 * (it & 3), (it >> 2) & 1); }
__device__ __forceinline__ void release(const Ctx& c, uint32_t it) {
  if (c.t < 2) asm volatile("mbarrier.arrive.shared::cluster.b64 _, [%0];" ::"r"(c.rel + 8 * (it & 3)) : "memory");
}
__device__ __forceinline__ uint64_t desc_of(uint32_t lo) {
  uint64_t d; asm volatile("mov.b64 %0, {%1, %2};" : "=l"(d) : "r"(lo), "r"(0x40000040)); return d;
}
__device__ __forceinline__ uint32_t desc_lo(const Ctx& c, uint32_t addr, uint32_t lbo) { return (addr >> 4) - c.d16 + ((lbo >> 4) << 16); }
template <bool INIT>
__device__ __forceinline__ void mma_step(const Ctx& c, float (&accA)[64], float (&accB)[64], uint32_t it) {
  const uint32_t st = desc_lo(c, c.sbase, 0) + (it & 3) * (STAGE_BYTES >> 4);
  const uint64_t da = desc_of(st + c.wg * 512 + (1 << 16)), db = desc_of(st + 1024 + (512 << 16));
  wgmma_fence();
#pragma unroll
  for (int kk = 0; kk < 4; kk++) wgmma_ss_n256(accA, accB, da + kk * 2, db + kk * 128, (INIT && kk == 0) ? 0 : 1);
  wgmma_commit();
}
__device__ __forceinline__ void stg_acquire(const Ctx& c) { mbar_wait(c.bars + 80 + c.wg * 8, (c.sc & 1) ^ 1); }
__device__ __forceinline__ void stg_commit(Ctx& c) {
  __syncwarp();
  if ((c.t & 31) == 0) mbar_arrive(c.bars + 64 + c.wg * 8);
  c.sc++;
}
template <int OFF>
__device__ __forceinline__ void box_write(const Ctx& c, uint32_t base, const uint32_t (&t)[64]) {
#pragma unroll
  for (int kk = 0; kk < 4; kk++)
    stmatrix_x4(base + c.st_off + (((kk * 2) ^ c.st_sw) << 4), t[OFF + 4 * kk], t[OFF + 4 * kk + 1], t[OFF + 4 * kk + 2], t[OFF + 4 * kk + 3]);
}
__device__ __forceinline__ void acc_write(const Ctx& c, uint32_t base, const float (&s)[64]) {
#pragma unroll
  for (int kk = 0; kk < 8; kk++)
    stmatrix_x4(base + (kk >> 2) * 8192 + c.st_off + ((((kk & 3) * 2) ^ c.st_sw) << 4), pack_bf16(s[8 * kk], s[8 * kk + 1]),
                pack_bf16(s[8 * kk + 2], s[8 * kk + 3]), pack_bf16(s[8 * kk + 4], s[8 * kk + 5]), pack_bf16(s[8 * kk + 6], s[8 * kk + 7]));
}
__device__ __forceinline__ uint32_t opaque(uint32_t v) { asm volatile("" : "+r"(v)); return v; }
__device__ __forceinline__ void half_store(Ctx& c, uint32_t (&t)[64]) {
  stg_acquire(c);
  const uint32_t stg = opaque(c.stg);
  box_write<0>(c, stg, t);
  box_write<16>(c, stg + 8192, t);
  fence_async_smem();
  stg_commit(c);
#pragma unroll
  for (int i = 0; i < 32; i++) asm volatile("mov.b32 %0, %1;" : "=r"(t[i]) : "r"(t[i + 32]));
}
__device__ __forceinline__ void final_half(const Ctx& c, const float (&acc)[64], uint32_t a, uint32_t pitch, const CUtensorMap* m, int col, int row, bool keep) {
  uint32_t g[32];
#pragma unroll
  for (int kk = 0; kk < 8; kk++)
    ldmatrix_x4(a + (kk >> 2) * pitch + c.st_off + ((((kk & 3) * 2) ^ c.st_sw) << 4), g[4 * kk], g[4 * kk + 1], g[4 * kk + 2], g[4 * kk + 3]);
#pragma unroll
  for (int i = 0; i < 32; i++) g[i] = pack_bf16(acc[2 * i] * bf_lo(g[i]), acc[2 * i + 1] * bf_hi(g[i]));
#pragma unroll
  for (int kk = 0; kk < 8; kk++)
    stmatrix_x4(a + (kk >> 2) * pitch + c.st_off + ((((kk & 3) * 2) ^ c.st_sw) << 4), g[4 * kk], g[4 * kk + 1], g[4 * kk + 2], g[4 * kk + 3]);
  fence_async_smem();
  bar_sync(3 + c.wg, 128);
  if (c.t == 0 && keep) {
    fence_async();
    asm volatile("cp.reduce.async.bulk.tensor.2d.global.shared::cta.add.bulk_group [%0, {%2, %3}], [%1];" ::"l"(m), "r"(a), "r"(col), "r"(row) : "memory");
    asm volatile("cp.reduce.async.bulk.tensor.2d.global.shared::cta.add.bulk_group [%0, {%2, %3}], [%1];" ::"l"(m), "r"(a + pitch), "r"(col + 64), "r"(row) : "memory");
    asm volatile("cp.async.bulk.commit_group;" ::: "memory");
  }
}
__device__ __forceinline__ void rotate16(uint32_t (&t)[64]) {
#pragma unroll
  for (int i = 0; i < 16; i++)
    asm volatile("{\n.reg .b32 v;\nmov.b32 v, %0;\nmov.b32 %0, %1;\nmov.b32 %1, %2;\nmov.b32 %2, %3;\nmov.b32 %3, v;\n}\n"
                 : "+r"(t[i]), "+r"(t[i + 16]), "+r"(t[i + 32]), "+r"(t[i + 48]));
}
__device__ __forceinline__ float quad_rcp_sum(float l) {
  l += __shfl_xor_sync(0xffffffffu, l, 1);
  l += __shfl_xor_sync(0xffffffffu, l, 2);
  float r; asm("rcp.approx.ftz.f32 %0, %1;" : "=f"(r) : "f"(l));
  return r;
}
template <int OFF>
__device__ __forceinline__ void capture_plain(uint32_t (&d)[64], const float (&s)[64]) {
#pragma unroll
  for (int i = 0; i < 32; i++) d[OFF + i] = pack_bf16(s[2 * i], s[2 * i + 1]);
}
template <int OFF>
__device__ __forceinline__ void capture_scaled(uint32_t (&d)[64], const float (&s)[64], float r0, float r1) {
#pragma unroll
  for (int i = 0; i < 32; i++) { const float r = (i & 1) ? r1 : r0; d[OFF + i] = pack_bf16(s[2 * i] * r, s[2 * i + 1] * r); }
}
template <int OFF>
__device__ __forceinline__ void capture_gate(uint32_t (&d)[64], const float (&s)[64], float b0, float b1) {
#pragma unroll
  for (int i = 0; i < 32; i++) {
    const float b = (i & 1) ? b1 : b0;
    d[OFF + i] = mul_bf2(pack_bf16(fmaf(s[2 * i], 0.5f, b), fmaf(s[2 * i + 1], 0.5f, b)), d[OFF + i]);
  }
}
template <int K0, int K1>
__device__ __forceinline__ void issue_qk(const Ctx& c, float (&s)[64], uint32_t qaddr, uint32_t it, int z = 0) {
  const uint64_t da = desc_of(desc_lo(c, qaddr, 16) + z), db = desc_of(desc_lo(c, c.sbase, 16) + (it & 3) * (STAGE_BYTES >> 4) + z);
  wgmma_fence();
#pragma unroll
  for (int kk = K0; kk < K1; kk++) wgmma_ss_n128<0>(s, da + (kk >> 2) * 512 + (kk & 3) * 2, db + (kk >> 2) * 1024 + (kk & 3) * 2, kk == 0 ? 0 : 1);
  wgmma_commit();
}
template <int K0, int K1>
__device__ __forceinline__ void issue_pv(const Ctx& c, float (&o)[64], uint32_t paddr, uint32_t it, int first_scale, int z = 0) {
  const uint64_t da = desc_of(desc_lo(c, paddr, 16) + z), db = desc_of(desc_lo(c, c.sbase, 16384) + (it & 3) * (STAGE_BYTES >> 4) + z);
  wgmma_fence();
#pragma unroll
  for (int kk = K0; kk < K1; kk++) wgmma_ss_n128<1>(o, da + (kk >> 2) * 512 + (kk & 3) * 2, db + kk * 128, kk == 0 ? first_scale : 1);
  wgmma_commit();
}
constexpr float SM_SCALE = 0.08838834764831845f * 1.4426950408889634f;
__device__ __forceinline__ void row_max(const float (&s)[64], int t0, int t1, float& x0, float& x1) {
  t0 = max(t0, __shfl_xor_sync(0xffffffffu, t0, 1)); t1 = max(t1, __shfl_xor_sync(0xffffffffu, t1, 1));
  t0 = max(t0, __shfl_xor_sync(0xffffffffu, t0, 2)); t1 = max(t1, __shfl_xor_sync(0xffffffffu, t1, 2));
  if (__builtin_expect(__any_sync(0xffffffffu, t0 == 0 || t1 == 0), 0)) {
    uint32_t u0 = 0xffffffffu, u1 = 0xffffffffu;
#pragma unroll
    for (int i = 0; i < 64; i += 4) {
      u0 = __vimin3_u32(u0, __float_as_uint(s[i]), __float_as_uint(s[i + 1]));
      u1 = __vimin3_u32(u1, __float_as_uint(s[i + 2]), __float_as_uint(s[i + 3]));
    }
    u0 = min(u0, __shfl_xor_sync(0xffffffffu, u0, 1)); u1 = min(u1, __shfl_xor_sync(0xffffffffu, u1, 1));
    u0 = min(u0, __shfl_xor_sync(0xffffffffu, u0, 2)); u1 = min(u1, __shfl_xor_sync(0xffffffffu, u1, 2));
    if (t0 == 0) t0 = (int)u0;
    if (t1 == 0) t1 = (int)u1;
  }
  x0 = __int_as_float(t0); x1 = __int_as_float(t1);
}
struct Att {
  float n0, n1, l0, l1, r0, r1;
  uint32_t it, pb, qb;
  bool rescale, landed;
};
template <int K0, int K1, int C0, int C1>
__device__ __forceinline__ void prob_part(const float (&s)[64], Att& a, const float (&sn)[64], int (&top)[2], uint32_t (&pk)[32]) {
#pragma unroll
  for (int kk = K0; kk < K1; kk++) {
    float e[8];
#pragma unroll
    for (int i = 0; i < 8; i++) asm volatile("ex2.approx.ftz.f32 %0, %1;" : "=f"(e[i]) : "f"(fmaf(s[8 * kk + i], SM_SCALE, (i & 2) ? a.n1 : a.n0)));
    a.l0 += (e[0] + e[1]) + (e[4] + e[5]);
    a.l1 += (e[2] + e[3]) + (e[6] + e[7]);
#pragma unroll
    for (int i = 0; i < 4; i++) asm volatile("cvt.rn.bf16x2.f32 %0, %1, %2;" : "=r"(pk[4 * kk + i]) : "f"(e[2 * i + 1]), "f"(e[2 * i]));
  }
#pragma unroll
  for (int i = 8 * C0; i < 8 * C1; i += 2)
    top[(i >> 1) & 1] = __vimax3_s32(top[(i >> 1) & 1], __float_as_int(sn[i]), __float_as_int(sn[i + 1]));
  asm volatile("" : "+f"(a.l0), "+f"(a.l1), "+r"(top[0]), "+r"(top[1]));
}
constexpr int AS1 = 2, AS2 = 7;
#define RARE(cond) __builtin_expect(!!(cond), 0)
#define ONCE(body) { int rep_ = 0; _Pragma("unroll 1") do { body; } while (++rep_ < c.one); }
template <int MODE, bool ODD>
__device__ __forceinline__ void att_step(Ctx& c, Att& a, int j, float (&s)[64], float (&sn)[64], float (&o)[64]) {
  int top[2] = {0, 0};
  uint32_t pk[32];
  const uint32_t itk = a.it + 1, itv = a.it + (MODE == 1 ? 2 : 1);
  a.it = itv;
  if (MODE != 0) {
    if (RARE(!a.landed)) {
      if (MODE == 1) wait_full(c, itk);
      wait_full(c, itv);
    }
    fence_async_smem();
    if (MODE == 1 && ODD && RARE(j == 5)) stg_commit(c);
    if (MODE == 1 && !ODD && RARE(j == 6)) stg_acquire(c);
    bar_sync(1 + c.wg, 256);
    if (MODE == 1) ONCE((issue_qk<0, 8>(c, sn, j < 3 ? c.stg : a.qb, itk, rep_)))
    else ONCE((issue_pv<0, 8>(c, o, a.pb, itv, 1, rep_), bar_arrive(2 - c.wg, 256)));
  }
  prob_part<0, AS1, 0, 0>(s, a, sn, top, pk);
  if (MODE == 1) ONCE((issue_pv<0, 8>(c, o, a.pb, itv, (j - 1) & 3, rep_), bar_arrive(2 - c.wg, 256)));
  if (MODE == 1) wgmma_wait<1>();
  if (MODE == 0) ONCE(wgmma_wait<0>());
  if (MODE != 2) release(c, itk);
  prob_part<AS1, AS2, 0, MODE != 2 ? 8 : 0>(s, a, sn, top, pk);
  if (MODE != 0) ONCE(wgmma_wait<0>());
  if (MODE != 0) release(c, itv);
  if (MODE == 0) wait_full(c, itv + 1 + c.wg);
  if (MODE == 1 && !ODD) a.pb = j == 6 ? c.stg : a.pb;
#pragma unroll
  for (int kk = 0; kk < AS2; kk++)
    stmatrix_x4(a.pb + (kk >> 2) * 8192 + c.st_off + ((((kk & 3) * 2) ^ c.st_sw) << 4), pk[4 * kk], pk[4 * kk + 1], pk[4 * kk + 2], pk[4 * kk + 3]);
  if (MODE != 2) a.landed = mbar_test2(c.bars + 8 * ((itv + 1) & 3), ((itv + 1) >> 2) & 1, c.bars + 8 * ((itv + 2) & 3), ((itv + 2) >> 2) & 1);
  prob_part<AS2, 8, 0, 0>(s, a, sn, top, pk);
#pragma unroll
  for (int kk = AS2; kk < 8; kk++)
    stmatrix_x4(a.pb + (kk >> 2) * 8192 + c.st_off + ((((kk & 3) * 2) ^ c.st_sw) << 4), pk[4 * kk], pk[4 * kk + 1], pk[4 * kk + 2], pk[4 * kk + 3]);
  const float t0 = (16.f - a.n0) * (1.f / SM_SCALE), t1 = (16.f - a.n1) * (1.f / SM_SCALE);
  const bool over = MODE != 2 && __any_sync(0xffffffffu, top[0] > __float_as_int(t0) || top[1] > __float_as_int(t1));
  const bool renew = MODE != 2 && ((ODD && j == 3) || over);
  if (!RARE(renew || (MODE != 0 && a.rescale))) return;
  if (MODE != 0 && a.rescale) {
#pragma unroll
    for (int i = 0; i < 16; i++) { o[4 * i] *= a.r0; o[4 * i + 1] *= a.r0; o[4 * i + 2] *= a.r1; o[4 * i + 3] *= a.r1; }
    a.rescale = false;
    if (MODE == 1 && !ODD && j == 4) acc_write(c, c.stg, o);
  }
  if (renew) {
    float x0, x1;
    row_max(sn, top[0], top[1], x0, x1);
    x0 *= -SM_SCALE; x1 *= -SM_SCALE;
    if (ODD && j == 3) {
      a.r0 = quad_rcp_sum(a.l0); a.r1 = quad_rcp_sum(a.l1);
      a.l0 = 0.f; a.l1 = 0.f;
    } else {
      x0 = fminf(x0, a.n0); x1 = fminf(x1, a.n1);
      a.r0 = ex2(x0 - a.n0); a.r1 = ex2(x1 - a.n1);
      a.l0 *= a.r0; a.l1 *= a.r1;
    }
    a.n0 = x0; a.n1 = x1;
    a.rescale = true;
  }
}

__device__ __forceinline__ void ln_stats(uint32_t (&t)[64], float& r0, float& b0, float& r1, float& b1, uint32_t zero) {
  float m0 = 0.f, m1 = 0.f;
#pragma unroll
  for (int i = 0; i < 16; i++) { m0 += bf_lo(t[i]) + bf_hi(t[i]); m1 += bf_lo(t[16 + i]) + bf_hi(t[16 + i]); }
#pragma unroll
  for (int o = 16; o > 0; o >>= 1) { m0 += __shfl_xor_sync(0xffffffffu, m0, o); m1 += __shfl_xor_sync(0xffffffffu, m1, o); }
  m0 *= 1.0f / DM; m1 *= 1.0f / DM;
#pragma unroll
  for (int i = 0; i < 32; i++) asm volatile("xor.b32 %0, %0, %1;" : "+r"(t[i]) : "r"(zero));
  float q0 = 0.f, q1 = 0.f;
#pragma unroll
  for (int i = 0; i < 16; i++) {
    const float a = bf_lo(t[i]) - m0, b = bf_hi(t[i]) - m0, c = bf_lo(t[16 + i]) - m1, d = bf_hi(t[16 + i]) - m1;
    q0 = fmaf(a, a, fmaf(b, b, q0)); q1 = fmaf(c, c, fmaf(d, d, q1));
  }
#pragma unroll
  for (int o = 16; o > 0; o >>= 1) { q0 += __shfl_xor_sync(0xffffffffu, q0, o); q1 += __shfl_xor_sync(0xffffffffu, q1, o); }
  r0 = rsqrtf(q0 * (1.0f / DM) + 1e-5f); b0 = -m0 * r0;
  r1 = rsqrtf(q1 * (1.0f / DM) + 1e-5f); b1 = -m1 * r1;
}
__device__ __forceinline__ uint32_t ln_apply(uint32_t w, float r, float b) { return pack_bf16(fmaf(bf_lo(w), r, b), fmaf(bf_hi(w), r, b)); }
__device__ __forceinline__ void ln_fixup(float (&acc)[64], uint32_t csum, float r0, float b0, float r1, float b1) {
#pragma unroll
  for (int j = 0; j < 16; j++) {
    float c0, c1;
    asm volatile("ld.shared.v2.f32 {%0, %1}, [%2];" : "=f"(c0), "=f"(c1) : "r"(csum + j * 32) : "memory");
    acc[4 * j] = fmaf(acc[4 * j], r0, b0 * c0); acc[4 * j + 1] = fmaf(acc[4 * j + 1], r0, b0 * c1);
    acc[4 * j + 2] = fmaf(acc[4 * j + 2], r1, b1 * c0); acc[4 * j + 3] = fmaf(acc[4 * j + 3], r1, b1 * c1);
  }
}

__device__ __forceinline__ unsigned long long tag_pack(float u, float v, uint32_t tag) {
  return ((unsigned long long)((__float_as_uint(u) + 128) >> 8) << 40) | ((unsigned long long)((__float_as_uint(v) + 128) >> 8) << 16) | tag;
}
__device__ __forceinline__ float4 tag_gather(const ulonglong2* src, int stride, int n, uint32_t tag) {
  float4 a = make_float4(0.f, 0.f, 0.f, 0.f);
  uint32_t spins = 0;
#pragma unroll 1
  for (int r = 0; r < n;) {
    unsigned long long u[8];
#pragma unroll
    for (int i = 0; i < 4; i++) {
      u[2 * i] = u[2 * i + 1] = tag;
      if (r + i < n) asm volatile("ld.relaxed.gpu.global.v2.u64 {%0, %1}, [%2];" : "=l"(u[2 * i]), "=l"(u[2 * i + 1]) : "l"(src + (r + i) * stride) : "memory");
    }
    bool ok = true;
#pragma unroll
    for (int i = 0; i < 8; i++) ok = ok && ((uint32_t)u[i] & 0xffffu) == tag;
    if (__all_sync(0xffffffffu, ok)) {
#pragma unroll
      for (int i = 0; i < 4; i++) {
        a.x += __uint_as_float((uint32_t)(u[2 * i] >> 32) & 0xffffff00u); a.y += __uint_as_float((uint32_t)(u[2 * i] >> 8) & 0xffffff00u);
        a.z += __uint_as_float((uint32_t)(u[2 * i + 1] >> 32) & 0xffffff00u); a.w += __uint_as_float((uint32_t)(u[2 * i + 1] >> 8) & 0xffffff00u);
      }
      r += 4;
    } else if (++spins > (1u << 22)) __trap();
  }
  return a;
}

struct Prod {
  uint32_t sbase, bars, it, rank, lane;
};
__device__ __forceinline__ uint32_t prod_acquire(Prod& p, uint32_t bytes) {
  uint32_t s = p.it & 3;
  mbar_wait_idle(p.bars + 32 + 8 * s, ((p.it >> 2) & 1) ^ 1);
  if (p.lane == 0) mbar_expect_tx(p.bars + 8 * s, bytes);
  p.it++;
  return s;
}
__device__ __forceinline__ void dep_wait(const Prod& p, uint32_t& ready, int base, int n, uint32_t target, int i) {
  if ((ready >> i) & 1) return;
  target *= launch_epoch();
  uint32_t spins = 0;
  do {
    const bool ok = (int)p.lane < n && (int)(ld_relaxed(&g_flags[base + p.lane]) - target) >= 0;
    ready = __ballot_sync(0xffffffffu, ok);
    if (++spins > (1u << 22)) __trap();
  } while (!((ready >> i) & 1));
  fence_acquire();
  __syncwarp();
  fence_async();
}
__device__ __forceinline__ void prod_gemm(Prod& p, const CUtensorMap* mA, int arow, const CUtensorMap* mB, int chunk, int k0, int k1,
                                          int base, int n, uint32_t target, int shift, uint32_t& ready) {
#pragma unroll 1
  for (int k = k0; k < k1; k++) {
    dep_wait(p, ready, base, n, target, k >> shift);
    uint32_t s = prod_acquire(p, STAGE_BYTES);
    uint32_t a = p.sbase + s * STAGE_BYTES;
    if (p.lane == 0) {
      tma_load_3d_mc(a + 16384 + p.rank * 16384, mB, p.bars + 8 * s, k * 64, chunk + p.rank * 2);
      tma_load_2d(a, mA, p.bars + 8 * s, k * 64, arow);
    }
  }
}

#define CTA_ROLE                                                   \
  uint32_t cta_;                                                   \
  asm volatile("mov.u32 %0, %%ctaid.x;" : "=r"(cta_));             \
  const bool regular = cta_ < 128;                                 \
  const int role = regular ? ((cta_ >> 1) - (cta_ >> 4)) & 7 : 8;  \
  const int mb0 = regular ? (cta_ >> 4) * 2 + (cta_ & 1) : cta_ & 3, mb_step = regular ? 0 : 4

__global__ void __cluster_dims__(2, 1, 1) __launch_bounds__(384, 1) mega_kernel(const __grid_constant__ Params P) {
  extern __shared__ __align__(1024) uint8_t smem_raw[];
  const uint32_t sbase = smem_u32(smem_raw);
  const uint32_t bars = sbase + SM_BAR;
  const int tid = threadIdx.x, lane = tid & 31;
  const int wg = __shfl_sync(0xffffffffu, tid >> 7, 0);
  const uint32_t rank = blockIdx.x & 1;
  if (tid == 256) {
    for (int s = 0; s < STAGES; s++) { mbar_init(bars + 8 * s, 1); mbar_init(bars + 32 + 8 * s, 4); }
    for (int w = 0; w < 2; w++) { mbar_init(bars + 64 + 8 * w, 4); mbar_init(bars + 80 + 8 * w, 1); mbar_init(bars + 96 + 8 * w, 5); mbar_init(bars + 112 + 8 * w, 4); }
    for (int w = 0; w < 2; w++) { mbar_init(bars + 144 + 8 * w, 1); }
    mbar_init(bars + 136, 1);
    mbar_init(bars + 160, 8);
    mbar_init(bars + 168, 3);
    mbar_init(bars + 176, 1);
    mbar_init(bars + 184, 1);
    asm volatile("fence.mbarrier_init.release.cluster;" ::: "memory");
  }

  __syncwarp();
  cluster_arrive_relaxed();

  if (wg == 2) {
    const int warp = __shfl_sync(0xffffffffu, tid >> 5, 0);
    CTA_ROLE;
    if (warp == 9 && lane < 2) asm volatile("prefetch.tensormap [%0];" ::"l"(&P.maps[lane ? M_X : role ? M_WIN : M_WQ]) : "memory");
    asm volatile("setmaxnreg.dec.sync.aligned.u32 40;");
    const uint32_t task0 = opaque(P.tasks[role][0]);
    cluster_wait();
    if (warp == 8) {
      Prod p{sbase, bars, 0, rank, (uint32_t)lane};
      if (regular) {
        const uint32_t task = __shfl_sync(0xffffffffu, task0, 0);
        uint32_t ready = 0xffffffffu;
        prod_gemm(p, &P.maps[M_X], mb0 * 128, &P.maps[(task & 15) == T_QA ? M_WQ : M_WIN],
                  ((task & 15) == T_Z2 ? FH / 64 : 0) + (task >> 4) * 4, 0, STAGES, 0, 0, 0, 5, ready);
      }
#pragma unroll 1
      for (int ti = 0; ti < MAXT; ti++) {
        const uint32_t task = P.tasks[role][ti];
        const int type = task & 15, idx = task >> 4, mb = (mb0 + ti * mb_step) & 15;
        if (type == T_NONE) break;
        const int arow = mb * 128;
        int mA = M_XN, mB = M_WIN, chunk = idx * 4, nk = 16, base = F_XN + mb, n = 1, shift = 5;
        uint32_t target = 8;
        int k0 = 0;
        if (type == T_Z2) chunk += FH / 64;
        else if (type == T_QA) mB = M_WQ;
        else if (type == T_G) { mA = M_WSP; mB = M_Z2; nk = 32; base = F_Z2N; n = 16; target = 14; shift = 1; }
        else if (type == T_S) { mA = M_O_LD; mB = M_WO; k0 = P.krange[role][0]; nk = P.krange[role][1]; base = F_O + mb * 32; n = 32; target = 2; shift = 1; }
        else if (type == T_Y) { mA = M_H_LD; mB = M_WOUT; nk = 28; base = F_H + mb * 8; n = 7; target = 2; shift = 2; }
        if (ti == 0 && regular) { mA = M_X; n = 0; k0 = STAGES; }
        uint32_t ready = n ? 0 : 0xffffffffu;
        prod_gemm(p, &P.maps[mA], arow, &P.maps[mB], chunk, k0, nk, base, n, target, shift, ready);
        if (type == T_QA) {
          const int kvrow = (idx >> 2) * SK + (SK - WIN);
#pragma unroll 1
          for (int j = 0; j < 16; j++) {
            const bool isK = j < 2 || (j < 14 && !(j & 1));
            const int ch = (j < 2 ? j : j >= 14 ? j - 12 : isK ? (j >> 1) + 1 : (j >> 1) - 1) & 3;
            uint32_t s = prod_acquire(p, 32768);
            if (lane == 0) tma_load_2d_mc(sbase + s * STAGE_BYTES + rank * 16384, &P.maps[isK ? M_K : M_V], bars + 8 * s, rank * 64, kvrow + ch * 128);
          }
        }
        if (type == T_S) {
          ready = 0;
          dep_wait(p, ready, F_SY + mb * 4 + idx, 1, 2, 0);
          const uint32_t s = prod_acquire(p, 32768);
          if (lane < 2) tma_load_2d(sbase + s * STAGE_BYTES + lane * 16384, &P.maps[M_SY_LD], bars + 8 * s, idx * 256 + 128 + lane * 64, arow);
        }
      }
    } else if (warp == 9 || warp == 10) {
      const int w = warp - 9;
      if (regular) {
        const uint32_t task = P.tasks[role][0];
        const int type = task & 15, tile = type == T_Z2 ? task >> 4 : 7, mb = mb0;
        const uint32_t slab = sbase + SM_STG + w * 16384;
        const uint32_t tag = launch_epoch() & 0xffffu;
        mbar_wait(bars + 136, 0);
        if (lane == 0) {
          const size_t off = (size_t)(blockIdx.x * 16 + w * 8) * DM;
          mbar_expect_tx(bars + 176 + 8 * w, 16384);
          asm volatile("cp.async.bulk.shared::cluster.global.mbarrier::complete_tx::bytes [%0], [%1], 16384, [%2];" ::"r"(slab), "l"(P.x + off), "r"(bars + 176 + 8 * w) : "memory");
          mbar_wait(bars + 96 + 8 * w, 0);
          fence_async_smem();
          mbar_expect_tx(bars + 176 + 8 * w, 16384);
          tma_load_3d(slab, &P.maps[type == T_QA ? M_WQ : M_WIN], bars + 176 + 8 * w, mb * 64, (type == T_Z2 ? FH / 64 : 0) + (task >> 4) * 4 + w * 2);
        }
        __syncwarp();
        mbar_wait(bars + 176 + 8 * w, 1);
        float4 a = make_float4(0.f, 0.f, 0.f, 0.f);
#pragma unroll 1
        for (int r = 0; r < 64; r += 8) {
          uint32_t v0[8], v1[8];
#pragma unroll
          for (int i = 0; i < 8; i++)
            asm volatile("ld.shared.v2.b32 {%0, %1}, [%2];" : "=r"(v0[i]), "=r"(v1[i]) : "r"(slab + (lane >> 4) * 8192 + (r + i) * 128 + ((((lane & 15) >> 1) ^ i) << 4) + (lane & 1) * 8) : "memory");
#pragma unroll
          for (int i = 0; i < 8; i += 2) {
            a.x += bf_lo(v0[i]) + bf_lo(v0[i + 1]); a.y += bf_hi(v0[i]) + bf_hi(v0[i + 1]);
            a.z += bf_lo(v1[i]) + bf_lo(v1[i + 1]); a.w += bf_hi(v1[i]) + bf_hi(v1[i + 1]);
          }
        }
        asm volatile("st.relaxed.gpu.global.v2.u64 [%0], {%1, %2};" ::"l"(&g_csum[(tile * 16 + mb) * 64 + w * 32 + lane]), "l"(tag_pack(a.x, a.y, tag)), "l"(tag_pack(a.z, a.w, tag)) : "memory");
        a = tag_gather(&g_csum[tile * 16 * 64 + w * 32 + lane], 64, 16, tag);
        asm volatile("st.shared.v4.f32 [%0], {%1, %2, %3, %4};" ::"r"(sbase + SM_CSUM + w * 512 + lane * 16), "f"(a.x), "f"(a.y), "f"(a.z), "f"(a.w) : "memory");
        __syncwarp();
        if (lane == 0) mbar_arrive(bars + 168);
        if (type == T_Z2) {
          mbar_wait_idle(bars + 112 + 8 * w, 0);
          a = tag_gather(reinterpret_cast<const ulonglong2*>(&g_stats[mb * 128 + w * 64 + lane * 2]), SEQ / 2, 7, tag);
          const float m0 = a.x * (1.0f / FH), m1 = a.z * (1.0f / FH);
          const float q0 = rsqrtf(fmaxf(fmaf(-m0, m0, a.y * (1.0f / FH)), 0.f) + 4e-5f);
          const float q1 = rsqrtf(fmaxf(fmaf(-m1, m1, a.w * (1.0f / FH)), 0.f) + 4e-5f);
          asm volatile("st.shared.v4.b32 [%0], {%1, %2, %3, %4};" ::"r"(sbase + SM_STAT + w * 512 + lane * 16), "r"(pack_bf16(q0, q0)), "r"(pack_bf16(-m0 * q0, -m0 * q0)),
                       "r"(pack_bf16(q1, q1)), "r"(pack_bf16(-m1 * q1, -m1 * q1)) : "memory");
          __syncwarp();
          if (lane == 0) mbar_arrive(bars + 144 + 8 * w);
        }
      }
      if (lane == 0) {
        uint32_t sc = 0;
#pragma unroll 1
        for (int ti = 0; ti < MAXT; ti++) {
          const uint32_t task = P.tasks[role][ti];
          const int type = task & 15, idx = task >> 4, mb = (mb0 + ti * mb_step) & 15;
          if (type == T_NONE) break;
          if (type == T_S) {
            flag_wait(F_SY + mb * 4 + idx, 2);
            fence_async();
            mbar_expect_tx(bars + 176 + 8 * w, 16384);
            tma_load_2d(sbase + SM_STG + w * 16384, &P.maps[M_SY_ST], bars + 176 + 8 * w, idx * 256, mb * 128 + w * 64);
            tma_load_2d(sbase + SM_STG + w * 16384 + 8192, &P.maps[M_SY_ST], bars + 176 + 8 * w, idx * 256 + 64, mb * 128 + w * 64);
            const bf16* po = P.out + (size_t)(mb * 128 + w * 64) * DM + idx * 256;
#pragma unroll 1
            for (int q = 0; q < 64; q++, po += DM)
              asm volatile("prefetch.global.L2 [%0];\nprefetch.global.L2 [%0 + 128];\nprefetch.global.L2 [%0 + 256];\nprefetch.global.L2 [%0 + 384];" ::"l"(po));
          }
          if (type == T_Z1 || type == T_S) continue;
          const int mi = type == T_Z2 ? M_Z2_ST : type == T_QA ? M_O_ST : type == T_G ? M_H_ST : M_SY_ST;
          const int f = type == T_Z2 ? F_Z2N + mb : type == T_QA ? F_O + mb * 32 + idx * 2 : type == T_G ? F_H + mb * 8 + idx : F_SY + mb * 4 + idx;
#pragma unroll 1
          for (int q = 0; q < 2; q++, sc++) {
            mbar_wait_idle(bars + 64 + w * 8, sc & 1);
            tma_store_2d(&P.maps[mi], sbase + SM_STG + w * 16384, idx * 256 + q * 128, mb * 128 + w * 64);
            tma_store_2d(&P.maps[mi], sbase + SM_STG + w * 16384 + 8192, idx * 256 + q * 128 + 64, mb * 128 + w * 64);
            asm volatile("cp.async.bulk.commit_group;" ::: "memory");
            asm volatile("cp.async.bulk.wait_group.read 0;" ::: "memory");
            mbar_arrive(bars + 80 + w * 8);
            if (q == 1 || type == T_QA) {
              asm volatile("cp.async.bulk.wait_group 0;" ::: "memory");
              red_release(&g_flags[f + (type == T_QA ? q : 0)]);
            }
          }
        }
      }
    } else {
      if (regular) {
        const int mb = mb0;
        {
          mbar_wait(bars + 136, 0);
          const size_t off = ((size_t)(blockIdx.x >> 5) * SK + (SK - WIN) + (blockIdx.x & 31) * 16) * 128 + lane * 64;
          asm volatile("prefetch.global.L2 [%0];" ::"l"(P.kv[0] + off));
          asm volatile("prefetch.global.L2 [%0];" ::"l"(P.kv[1] + off));
        }
        if (lane == 0) {
          mbar_wait(bars + 176, 0);
          mbar_wait(bars + 184, 0);
          asm volatile("cp.async.bulk.global.shared::cta.bulk_group [%0], [%1], 32768;" ::"l"(P.out + (size_t)blockIdx.x * 16 * DM), "r"(sbase + SM_STG) : "memory");
          asm volatile("cp.async.bulk.commit_group;" ::: "memory");
          asm volatile("cp.async.bulk.wait_group.read 0;" ::: "memory");
          mbar_arrive(bars + 96);
          mbar_arrive(bars + 104);
          asm volatile("cp.async.bulk.wait_group 0;" ::: "memory");
        }
        __syncwarp();
        mbar_wait(bars + 160, 0);
        if (lane == 0) red_release(&g_flags[F_XN + (blockIdx.x >> 3)]);
        __syncwarp();
        if (lane == 0) asm volatile("st.shared.u32 [%0], %1;" ::"r"(bars + 128), "r"(launch_epoch()) : "memory");
        flag_wait(F_XN + mb, 8);
        const float4 u0 = __ldcg(reinterpret_cast<const float4*>(&g_xstat[mb * 128]) + lane);
        const float4 u1 = __ldcg(reinterpret_cast<const float4*>(&g_xstat[mb * 128 + 64]) + lane);
        asm volatile("st.shared.v4.f32 [%0], {%1, %2, %3, %4};" ::"r"(sbase + SM_STAT + lane * 16), "f"(u0.x), "f"(u0.y), "f"(u0.z), "f"(u0.w) : "memory");
        asm volatile("st.shared.v4.f32 [%0], {%1, %2, %3, %4};" ::"r"(sbase + SM_STAT + 512 + lane * 16), "f"(u1.x), "f"(u1.y), "f"(u1.z), "f"(u1.w) : "memory");
        __syncwarp();
        if (lane == 0) mbar_arrive(bars + 168);
      }
    }
  } else {
    asm volatile("setmaxnreg.inc.sync.aligned.u32 232;");
    const int warp = tid >> 5;
    CTA_ROLE;
    const int mb = mb0;
    (void)mb_step;
    uint32_t t[64];
#pragma unroll
    for (int i = 0; i < 64; i++) t[i] = 0;
    cluster_wait();
    Ctx c;
    c.sbase = sbase; c.bars = bars; c.it = 0; c.sc = 0; c.wg = wg; c.t = tid & 127; c.one = P.one;
    c.d16 = (sbase & ~0x3FFFFu) >> 4;
    asm volatile("mapa.shared::cluster.u32 %0, %1, %2;" : "=r"(c.rel) : "r"(bars + 32), "r"(tid & 1));
    c.stg = sbase + SM_STG + wg * 16384;
    {
      const int row = (warp & 3) * 16 + ((lane >> 3) & 1) * 8 + (lane & 7);
      c.st_off = row * 128;
      c.st_sw = (lane >> 4) ^ (lane & 7);
    }
    if (wg == 1) bar_arrive(1, 256);
    float accA[64], accB[64];
    int pend = 2, ptype = T_NONE;
    float s0 = 0.f, s1 = 0.f, q0 = 0.f, q1 = 0.f;
    wait_full(c, 0);
    if (tid == 0) mbar_arrive(bars + 136);
    mma_step<true>(c, accA, accB, 0);
#pragma unroll 1
    for (int ti = 0;; ti++) {
      const uint32_t task = P.tasks[role][ti];
      const int type = task & 15;
      const bool is_qa = type == T_QA;
      uint32_t it = c.it + 1;
      const uint32_t nk = type == T_G ? 32 : type == T_Y ? 28 : (type == T_S) ? P.krange[role][1] - P.krange[role][0] : 16;
      const uint32_t last = c.it + nk - 1;
      const uint32_t period = type == T_G ? 4 : (ti == 0 || (ptype == T_Y && nk >= 26)) ? 3 : 2;
      const bool raw = ti == 0 && regular;
      uint32_t slot = ti == 0 && !regular ? last : it + (wg ? period >> 1 : 0) + (raw ? LN_DELAY : ptype == T_QA ? 1 : 0);
#pragma unroll 1
      for (; it < last; it++) {
        wait_full(c, it);
        mma_step<false>(c, accA, accB, it);
        wgmma_wait<1>();
        release(c, it - 1);
        if (it == slot) {
          const uint32_t stat = sbase + SM_STAT + (wg * 64 + (warp & 3) * 16 + (lane >> 2)) * 8;
          slot += period;
          if (pend > 2) {
            if (ptype == T_Y) {
#pragma unroll
              for (int i = 0; i < 16; i++) t[i] = pack_bf16(silu(bf_lo(t[i])), silu(bf_hi(t[i])));
            } else {
#pragma unroll
              for (int i = 0; i < 16; i++) {
                const float a = gelu2_tanh(bf_lo(t[i])), b = gelu2_tanh(bf_hi(t[i]));
                t[i] = pack_bf16(a, b);
                if (i & 1) { s1 += a + b; q1 = fmaf(a, a, fmaf(b, b, q1)); }
                else { s0 += a + b; q0 = fmaf(a, a, fmaf(b, b, q0)); }
              }
            }
            rotate16(t);
            if (pend == 3) {
              if (ptype == T_Z1) {
                const bf16* bp = P.b_sp + mb * 128 + wg * 64 + (warp & 3) * 16 + (lane >> 2);
                s0 = 0.5f * __bfloat162float(bp[0]); s1 = 0.5f * __bfloat162float(bp[8]);
                pend = 1;
              } else if (ptype == T_Z2) {
                slot += period;
#pragma unroll
                for (int o = 1; o < 4; o <<= 1) {
                  s0 += __shfl_xor_sync(0xffffffffu, s0, o); q0 += __shfl_xor_sync(0xffffffffu, q0, o);
                  s1 += __shfl_xor_sync(0xffffffffu, s1, o); q1 += __shfl_xor_sync(0xffffffffu, q1, o);
                }
                if ((lane & 3) < 2) {
                  const uint32_t t0 = P.tasks[role][0];
                  const int row = mb * 128 + wg * 64 + (warp & 3) * 16 + (lane >> 2) + (lane & 1) * 8;
                  uint32_t epoch;
                  asm volatile("ld.shared.u32 %0, [%1];" : "=r"(epoch) : "r"(bars + 128) : "memory");
                  asm volatile("st.relaxed.gpu.global.u64 [%0], %1;" ::"l"(&g_stats[(t0 >> 4) * SEQ + row]),
                               "l"(tag_pack((lane & 1) ? s1 : s0, (lane & 1) ? q1 : q0, epoch & 0xffffu)) : "memory");
                }
                __syncwarp();
                if (lane == 0) mbar_arrive(bars + 112 + 8 * wg);
              }
            }
          } else if (ptype == T_NONE) {
            if (pend == 2) {
              mbar_wait(bars + 176 + 8 * wg, 0);
#pragma unroll
              for (int i = 0; i < 8; i++)
                asm volatile("ld.shared.v4.u32 {%0, %1, %2, %3}, [%4];" : "=r"(t[4 * i]), "=r"(t[4 * i + 1]), "=r"(t[4 * i + 2]), "=r"(t[4 * i + 3]) : "r"(c.stg + (warp & 3) * 4096 + i * 512 + lane * 16) : "memory");
              __syncwarp();
              if (lane == 0) mbar_arrive(bars + 96 + 8 * wg);
              ln_stats(t, s0, q0, s1, q1, t[32]);
            }
            if (pend == 1) {
              const int row = blockIdx.x * 16 + warp * 2;
              uint4* xo = reinterpret_cast<uint4*>(g_xn + (size_t)row * DM);
#pragma unroll
              for (int i = 0; i < 8; i++) {
                const float r = i < 4 ? s0 : s1, b = i < 4 ? q0 : q1;
                xo[i * 32 + lane] = make_uint4(ln_apply(t[4 * i], r, b), ln_apply(t[4 * i + 1], r, b), ln_apply(t[4 * i + 2], r, b), ln_apply(t[4 * i + 3], r, b));
              }
              if (lane == 0) *reinterpret_cast<float4*>(&g_xstat[row]) = make_float4(s0, q0, s1, q1);
              __syncwarp();
              if (lane == 0) mbar_arrive(bars + 160);
            }
          } else {
            if (ptype == T_Z2) {
              uint32_t a0, b0, a1, b1;
              mbar_wait(bars + 144 + 8 * wg, 0);
              asm volatile("ld.shared.v2.b32 {%0, %1}, [%2];" : "=r"(a0), "=r"(b0) : "r"(stat) : "memory");
              asm volatile("ld.shared.v2.b32 {%0, %1}, [%2];" : "=r"(a1), "=r"(b1) : "r"(stat + 64) : "memory");
#pragma unroll
              for (int i = 0; i < 32; i++) t[i] = fma_bf2(t[i], (i & 1) ? a1 : a0, (i & 1) ? b1 : b0);
            }
            half_store(c, t);
          }
          if (--pend == 0) slot = last;
        }
      }
      wait_full(c, it);
      if (is_qa) stg_acquire(c);
      bar_sync(1 + wg, 256);
      mma_step<false>(c, accA, accB, it);
      bar_arrive(2 - wg, 256);
      wgmma_wait<1>();
      release(c, it - 1);
      wgmma_wait<0>();
      release(c, it);
      it++;
      if (type == T_S) {
        const int col = (task >> 4) * 256, row = mb * 128 + wg * 64;
        mbar_wait(bars + 176 + 8 * wg, 0);
#pragma unroll 1
        for (int h = 0;; h++) {
          final_half(c, accA, h ? stage_addr(c, it) + wg * 8192 : c.stg, h ? 16384 : 8192, &P.maps[M_OUT], col + h * 128, row, regular);
          if (h) break;
#pragma unroll
          for (int i = 0; i < 64; i++) accA[i] = accB[i];
          wait_full(c, it);
        }
        if (c.t == 0) asm volatile("cp.async.bulk.wait_group.read 0;" ::: "memory");
        break;
      }
      if (raw) {
        const uint32_t stat = sbase + SM_STAT + (wg * 64 + (warp & 3) * 16 + (lane >> 2)) * 8;
        mbar_wait(bars + 168, 0);
        asm volatile("ld.shared.v2.f32 {%0, %1}, [%2];" : "=f"(s0), "=f"(q0) : "r"(stat) : "memory");
        asm volatile("ld.shared.v2.f32 {%0, %1}, [%2];" : "=f"(s1), "=f"(q1) : "r"(stat + 64) : "memory");
        ln_fixup(accA, sbase + SM_CSUM + (lane & 3) * 8, s0, q0, s1, q1);
        ln_fixup(accB, sbase + SM_CSUM + 512 + (lane & 3) * 8, s0, q0, s1, q1);
      }
      if (is_qa) {
        acc_write(c, opaque(c.stg), accA);
        Att a;
        a.qb = stage_addr(c, it + wg) + 32768;
        a.pb = stage_addr(c, it + 2 + wg) + 32768;
        float sa[64], sb[64], o[64];
#pragma unroll
        for (int i = 0; i < 64; i++) { sa[i] = 0.f; sb[i] = 0.f; }
        wait_full(c, it);
        wait_full(c, it + 1);
        fence_async_smem();
        bar_sync(1 + wg, 256);
        issue_qk<0, 8>(c, sa, c.stg, it);
        acc_write(c, a.qb, accB);
        issue_qk<0, 8>(c, sb, c.stg, it + 1);
        bar_arrive(2 - wg, 256);
        wgmma_wait<1>();
        release(c, it);
        a.it = it; a.l0 = 0.f; a.l1 = 0.f; a.r0 = 0.f; a.r1 = 0.f; a.rescale = false;
        {
          float x0, x1;
          int m[4] = {0, 0, 0, 0};
#pragma unroll
          for (int i = 0; i < 64; i += 2) m[(i >> 1) & 3] = __vimax3_s32(m[(i >> 1) & 3], __float_as_int(sa[i]), __float_as_int(sa[i + 1]));
          row_max(sa, max(m[0], m[2]), max(m[1], m[3]), x0, x1);
          a.n0 = -x0 * SM_SCALE; a.n1 = -x1 * SM_SCALE;
        }
        att_step<0, false>(c, a, 0, sa, sb, o);
#pragma unroll
        for (int i = 0; i < 64; i++) o[i] = 0.f;
#pragma unroll 1
        for (int j = 1; j < 7; j += 2) {
          att_step<1, true>(c, a, j, sb, sa, o);
          att_step<1, false>(c, a, j + 1, sa, sb, o);
        }
        att_step<2, true>(c, a, 7, sb, sa, o);
        it = a.it + 1;
        wait_full(c, it);
        fence_async_smem();
        bar_sync(1 + wg, 256);
        issue_pv<0, 8>(c, o, a.pb, it, 1);
        it++;
#pragma unroll
        for (int i = 0; i < 64; i++) { accA[i] = 0.f; accB[i] = 0.f; }
        wait_full(c, it);
        mma_step<true>(c, accA, accB, it);
        bar_arrive(2 - wg, 256);
        const float r0 = quad_rcp_sum(a.l0), r1 = quad_rcp_sum(a.l1);
        wgmma_wait<1>();
        release(c, it - 1);
        capture_scaled<0>(t, o, r0, r1);
#pragma unroll
        for (int i = 32; i < 64; i++) t[i] = 0;
      } else {
        if (type == T_G) {
          capture_gate<0>(t, accA, s0, s1);
          capture_gate<32>(t, accB, s0, s1);
        } else {
          capture_plain<0>(t, accA);
          capture_plain<32>(t, accB);
        }
        wait_full(c, it);
        mma_step<true>(c, accA, accB, it);
      }
      c.it = it;
      s0 = 0.f; s1 = 0.f; q0 = 0.f; q1 = 0.f;
      pend = is_qa ? 1 : (type == T_Z2 || type == T_Z1 || type == T_Y) ? 6 : 2;
      ptype = type;
    }
    wgmma_wait<0>();
  }
  __syncwarp();
  cluster_arrive_relaxed();
  cluster_wait();
  if (tid == 0) asm volatile("red.relaxed.gpu.global.add.u32 [%0], 1;" ::"l"(&g_flags[F_EPOCH + blockIdx.x]) : "memory");
}

typedef CUresult (*PFN_encodeTiled)(CUtensorMap*, CUtensorMapDataType, cuuint32_t, void*, const cuuint64_t*, const cuuint64_t*, const cuuint32_t*,
                                    const cuuint32_t*, CUtensorMapInterleave, CUtensorMapSwizzle, CUtensorMapL2promotion, CUtensorMapFloatOOBfill);

static void map_2d(PFN_encodeTiled enc, CUtensorMap* m, const void* ptr, uint64_t rows, uint64_t cols, uint32_t box_rows = 128) {
  cuuint64_t dims[2] = {cols, rows}; cuuint64_t strides[1] = {cols * 2};
  cuuint32_t box[2] = {64, box_rows}; cuuint32_t es[2] = {1, 1};
  enc(m, CU_TENSOR_MAP_DATA_TYPE_BFLOAT16, 2, const_cast<void*>(ptr), dims, strides, box, es, CU_TENSOR_MAP_INTERLEAVE_NONE,
      CU_TENSOR_MAP_SWIZZLE_128B, CU_TENSOR_MAP_L2_PROMOTION_L2_256B, CU_TENSOR_MAP_FLOAT_OOB_FILL_NONE);
}
static void map_3d(PFN_encodeTiled enc, CUtensorMap* m, const void* ptr, uint64_t rows, uint64_t cols) {
  cuuint64_t dims[3] = {64, rows, cols / 64}; cuuint64_t strides[2] = {cols * 2, 128};
  cuuint32_t box[3] = {64, 64, 2}; cuuint32_t es[3] = {1, 1, 1};
  enc(m, CU_TENSOR_MAP_DATA_TYPE_BFLOAT16, 3, const_cast<void*>(ptr), dims, strides, box, es, CU_TENSOR_MAP_INTERLEAVE_NONE,
      CU_TENSOR_MAP_SWIZZLE_128B, CU_TENSOR_MAP_L2_PROMOTION_L2_256B, CU_TENSOR_MAP_FLOAT_OOB_FILL_NONE);
}
static unsigned char mk(int type, int idx) { return (unsigned char)(type | (idx << 4)); }

static void build_schedule(Params& P, bool spare = true) {
  static const char* const plan66[9] = {
      "q0 h2 q9 y1 s1:40-64",
      "z0 q1 q6 q10 y0 s0:43-64",
      "z1 q2 h5 y2 s0:0-43",
      "z2 q3 h6 y3 s1:0-40",
      "z3 q4 h3 q11 s2:0-34",
      "z4 h0 q7 q13 s2:34-64",
      "z5 q5 h4 q12 s3:0-34",
      "z6 h1 q8 q14 s3:34-64",
      "q15 q15 q15 q15 s2:0-5",
  };
  static const char* const plan64[9] = {
      "q0 h1 q9 y0 s0:37-64",
      "z0 q1 h2 q12 s0:0-37",
      "z2 q3 q7 q10 y1 s1:40-64",
      "z1 q2 h3 q13 s1:0-40",
      "z4 q5 q8 q11 y2 s2:40-64",
      "z3 q4 h4 q14 s2:0-40",
      "z6 h0 h6 y3 s3:37-64",
      "z5 q6 h5 q15 s3:0-37",
      "",
  };
  const char* const* plan = spare ? plan66 : plan64;
  for (int j = 0; j < 9; j++) {
    P.krange[j][0] = P.krange[j][1] = 0;
    unsigned char* T = P.tasks[j];
    int n = 0;
    for (const char* q = plan[j]; *q;) {
      const char kind = *q++;
      int v[3] = {0, 0, 0};
      for (int f = 0; *q && *q != ' '; q++) {
        if (*q == ':' || *q == '-') f++;
        else v[f] = v[f] * 10 + (*q - '0');
      }
      while (*q == ' ') q++;
      if (kind == 'z') T[n++] = mk(T_Z2, v[0]);
      else if (kind == 'q') T[n++] = mk(T_QA, v[0]);
      else if (kind == 'h') { T[n++] = mk(T_Z1, v[0]); T[n++] = mk(T_G, v[0]); }
      else if (kind == 'y') T[n++] = mk(T_Y, v[0]);
      else { T[n++] = mk(T_S, v[0]); P.krange[j][0] = (unsigned char)v[1]; P.krange[j][1] = (unsigned char)v[2]; }
    }
    while (n < MAXT) T[n++] = 0;
  }
}

extern "C" void kernel_launch(void* const* d_in, const int* in_sizes, int n_in, void* d_out, int out_size) {
  (void)in_sizes; (void)n_in; (void)out_size;
  static PFN_encodeTiled enc = nullptr;
  static void *p_xn, *p_z2, *p_o, *p_h, *p_sy;
  static int clusters = 64;
  if (!enc) {
    void* fn = nullptr; cudaDriverEntryPointQueryResult qr;
    cudaGetDriverEntryPoint("cuTensorMapEncodeTiled", &fn, cudaEnableDefault, &qr);
    enc = (PFN_encodeTiled)fn;
    cudaGetSymbolAddress(&p_xn, g_xn); cudaGetSymbolAddress(&p_z2, g_z2); cudaGetSymbolAddress(&p_o, g_o);
    cudaGetSymbolAddress(&p_h, g_h); cudaGetSymbolAddress(&p_sy, g_sy);
    cudaFuncSetAttribute(mega_kernel, cudaFuncAttributeMaxDynamicSharedMemorySize, SMEM_BYTES);
    cudaLaunchConfig_t cfg = {};
    cfg.gridDim = dim3(NCLUSTERS * 2); cfg.blockDim = dim3(384); cfg.dynamicSmemBytes = SMEM_BYTES;
    cudaLaunchAttribute at;
    at.id = cudaLaunchAttributeClusterDimension; at.val.clusterDim.x = 2; at.val.clusterDim.y = 1; at.val.clusterDim.z = 1;
    cfg.attrs = &at; cfg.numAttrs = 1;
    int fit = 0;
    if (cudaOccupancyMaxActiveClusters(&fit, mega_kernel, &cfg) == cudaSuccess && fit >= NCLUSTERS) clusters = NCLUSTERS;
    (void)cudaGetLastError();
  }
  Params P;
  map_2d(enc, &P.maps[M_XN], p_xn, SEQ, DM);
  map_2d(enc, &P.maps[M_WSP], d_in[7], SEQ, SEQ);
  map_2d(enc, &P.maps[M_O_LD], p_o, SEQ, HD);
  map_2d(enc, &P.maps[M_H_LD], p_h, SEQ, FH);
  map_2d(enc, &P.maps[M_X], d_in[0], SEQ, DM);
  map_2d(enc, &P.maps[M_SY_LD], p_sy, SEQ, DM);
  map_2d(enc, &P.maps[M_K], d_in[1], 4 * SK, 128);
  map_2d(enc, &P.maps[M_V], d_in[2], 4 * SK, 128);
  map_3d(enc, &P.maps[M_WIN], d_in[6], DM, FF);
  map_3d(enc, &P.maps[M_WQ], d_in[3], DM, HD);
  map_3d(enc, &P.maps[M_Z2], p_z2, SEQ, FH);
  map_3d(enc, &P.maps[M_WO], d_in[4], HD, DM);
  map_3d(enc, &P.maps[M_WOUT], d_in[9], FH, DM);
  map_2d(enc, &P.maps[M_Z2_ST], p_z2, SEQ, FH, 64);
  map_2d(enc, &P.maps[M_O_ST], p_o, SEQ, HD, 64);
  map_2d(enc, &P.maps[M_H_ST], p_h, SEQ, FH, 64);
  map_2d(enc, &P.maps[M_SY_ST], p_sy, SEQ, DM, 64);
  map_2d(enc, &P.maps[M_OUT], d_out, SEQ, DM, 64);
  P.x = (const bf16*)d_in[0];
  P.out = (bf16*)d_out;
  P.b_sp = (const bf16*)d_in[8];
  P.kv[0] = (const bf16*)d_in[1];
  P.kv[1] = (const bf16*)d_in[2];
  P.one = 1;
  build_schedule(P, clusters == NCLUSTERS);
  mega_kernel<<<clusters * 2, 384, SMEM_BYTES, cudaStreamPerThread>>>(P);
}
```
